```python
import torch

def _softmax(x, axis=-1):
    return torch.softmax(x, dim=axis)
def _gelu(x):
    return torch.nn.functional.gelu(x, approximate="tanh")
def _silu(x):
    return torch.nn.functional.silu(x)
def _sigmoid(x):
    return torch.sigmoid(x)
def _layernorm(x, axis=-1, eps=1e-5):
    m = x.mean(dim=axis, keepdim=True)
    v = x.var(dim=axis, keepdim=True, unbiased=False)
    return (x - m) / torch.sqrt(v + eps)
def _scatter_add(tgt, idx, src, axis=0):
    return tgt.clone().index_add_(axis, idx, src)
def _segment_sum(src, seg, n):
    out = torch.zeros((n,) + src.shape[1:], dtype=src.dtype)
    return out.index_add_(0, seg, src)
def _pad(x, pw):
    flat = tuple(v for pair in reversed(pw) for v in pair)
    return torch.nn.functional.pad(x, flat)

kernel_name = 'parallel_sum__ssm_conv_s4__glu_gated_swiglu__prompt'

def setup_inputs():

    _w = (lambda a: (lambda t: t.to(torch.bfloat16) if t.is_floating_point() else t)(torch.as_tensor(a)))
    def _A_setup():
        B, L, D, N = 1, 2048, 576, 128
        A_re = -(lambda _x: torch.exp(torch.as_tensor(_x)))((lambda *s: torch.randn(*s, dtype=torch.bfloat16) * 6.4)(D, N))
        A_im = torch.pi * (lambda *s: torch.randn(*s, dtype=torch.bfloat16) * 0.05)(D, N)
        B_re = (lambda *s: torch.randn(*s, dtype=torch.bfloat16) * 0.1)(D, N)
        B_im = (lambda *s: torch.randn(*s, dtype=torch.bfloat16) * 0.1)(D, N)
        C_re = (lambda *s: torch.randn(*s, dtype=torch.bfloat16) * 0.1)(D, N)
        C_im = (lambda *s: torch.randn(*s, dtype=torch.bfloat16) * 0.1)(D, N)
        log_dt = (lambda *s: torch.randn(*s, dtype=torch.bfloat16) * 0.05)(D) * 0.5 - 4.0
        Dskip = (lambda *s: torch.randn(*s, dtype=torch.bfloat16) * 0.05)(D)
        return {
            "u": _w((lambda *s: torch.randn(*s, dtype=torch.bfloat16) * 0.05)(B, L, D)),
            "A_re": _w(A_re),
            "A_im": _w(A_im),
            "B_re": _w(B_re),
            "B_im": _w(B_im),
            "C_re": _w(C_re),
            "C_im": _w(C_im),
            "log_dt": _w(log_dt),
            "Dskip": _w(Dskip),
        }
    _A_in = _A_setup()

    def _B_setup():
        B, S, D, F = 1, 2048, 576, 4608
        return {
            "x": _w((lambda *s: torch.randn(*s, dtype=torch.bfloat16) * 0.05)(B, S, D)),
            "w1": _w((lambda *s: torch.randn(*s, dtype=torch.bfloat16) * 0.4)(D, F) * (2.0 / D) ** 0.5),
            "w3": _w((lambda *s: torch.randn(*s, dtype=torch.bfloat16) * 0.4)(D, F) * (2.0 / D) ** 0.5),
            "w2": _w((lambda *s: torch.randn(*s, dtype=torch.bfloat16) * 0.4)(F, D) * (2.0 / F) ** 0.5),
        }
    _B_in = _B_setup()

    return {
        "A_u": _A_in["u"],
        "A_A_re": _A_in["A_re"],
        "A_A_im": _A_in["A_im"],
        "A_B_re": _A_in["B_re"],
        "A_B_im": _A_in["B_im"],
        "A_C_re": _A_in["C_re"],
        "A_C_im": _A_in["C_im"],
        "A_log_dt": _A_in["log_dt"],
        "A_Dskip": _A_in["Dskip"],
        "B_x": _B_in["x"],
        "B_w1": _B_in["w1"],
        "B_w3": _B_in["w3"],
        "B_w2": _B_in["w2"],
    }

def reference(A_u, A_A_re, A_A_im, A_B_re, A_B_im, A_C_re, A_C_im, A_log_dt, A_Dskip, B_x, B_w1, B_w3, B_w2):
    def _A_ref(u, A_re, A_im, B_re, B_im, C_re, C_im, log_dt, Dskip):
        Bsz, L, D = u.shape
        dt = torch.exp(log_dt)[:, None]
        A = A_re + 1j * A_im
        Bc = B_re + 1j * B_im
        Cc = C_re + 1j * C_im
        logdA = dt * A
        dB = dt * Bc
        l = (lambda x, dt: x.to(dt))(torch.arange(L), A_re.dtype)
        P = torch.exp(logdA[:, :, None] * l[None, None, :])
        K = torch.einsum("dn,dnl,dn->dl", Cc, P, dB).real
        L2 = 2 * L
        Kp = _pad(K, ((0, 0), (0, L)))
        up = (lambda x, *d: x.permute(*d))(u, 0, 2, 1)
        up = _pad(up, ((0, 0), (0, 0), (0, L)))
        Kf = (lambda x, axes=(-2,-1): torch.fft.rfft2(x.float(), dim=axes))(Kp[:, None, :], axes=(-2, -1))
        Uf = (lambda x, axes=(-2,-1): torch.fft.rfft2(x.float(), dim=axes))(up[:, :, None, :], axes=(-2, -1))
        Yf = Uf * Kf[None, :, :, :]
        y = (lambda x, s, axes=(-2,-1): torch.fft.irfft2(x, s=s, dim=axes).to(torch.bfloat16))(Yf, (1, L2), axes=(-2, -1))[:, :, 0, :L]
        y = (lambda x, *d: x.permute(*d))(y, 0, 2, 1) + u * Dskip[None, None, :]
        return y

    def _B_ref(x, w1, w3, w2):
        gate = torch.einsum("bsd,df->bsf", x, w1)
        up = torch.einsum("bsd,df->bsf", x, w3)
        h = _silu(gate) * up
        out = torch.einsum("bsf,fd->bsd", h, w2)
        return out

    x = A_u
    xn = _layernorm(x, axis=-1)
    return x + _A_ref(xn, A_A_re, A_A_im, A_B_re, A_B_im, A_C_re, A_C_im, A_log_dt, A_Dskip) + _B_ref(xn, B_w1, B_w3, B_w2)
```

```cpp
#include <cuda_runtime.h>
#include <cuda.h>
#include <cuda_bf16.h>
#include <stdint.h>
#include <stdio.h>

__device__ __forceinline__ void wgmma_rs_n64_t1(float* d, uint32_t a0, uint32_t a1, uint32_t a2, uint32_t a3, uint64_t descB, int scaleD) {
  asm volatile("{\n.reg .pred p;\nsetp.ne.b32 p, %37, 0;\n"
    "wgmma.mma_async.sync.aligned.m64n64k16.f32.bf16.bf16 {%0,%1,%2,%3,%4,%5,%6,%7,%8,%9,%10,%11,%12,%13,%14,%15,%16,%17,%18,%19,%20,%21,%22,%23,%24,%25,%26,%27,%28,%29,%30,%31}, {%32,%33,%34,%35}, %36, p, 1, 1, 1;\n}\n"
    : "+f"(d[0]), "+f"(d[1]), "+f"(d[2]), "+f"(d[3]), "+f"(d[4]), "+f"(d[5]), "+f"(d[6]), "+f"(d[7]), "+f"(d[8]), "+f"(d[9]), "+f"(d[10]), "+f"(d[11]), "+f"(d[12]), "+f"(d[13]), "+f"(d[14]), "+f"(d[15]), "+f"(d[16]), "+f"(d[17]), "+f"(d[18]), "+f"(d[19]), "+f"(d[20]), "+f"(d[21]), "+f"(d[22]), "+f"(d[23]), "+f"(d[24]), "+f"(d[25]), "+f"(d[26]), "+f"(d[27]), "+f"(d[28]), "+f"(d[29]), "+f"(d[30]), "+f"(d[31])
    : "r"(a0), "r"(a1), "r"(a2), "r"(a3), "l"(descB), "r"(scaleD));
}
__device__ __forceinline__ void wgmma_ss_n48_t0(float* d, uint64_t descA, uint64_t descB, int scaleD) {
  asm volatile("{\n.reg .pred p;\nsetp.ne.b32 p, %26, 0;\n"
    "wgmma.mma_async.sync.aligned.m64n48k16.f32.bf16.bf16 {%0,%1,%2,%3,%4,%5,%6,%7,%8,%9,%10,%11,%12,%13,%14,%15,%16,%17,%18,%19,%20,%21,%22,%23}, %24, %25, p, 1, 1, 0, 0;\n}\n"
    : "+f"(d[0]), "+f"(d[1]), "+f"(d[2]), "+f"(d[3]), "+f"(d[4]), "+f"(d[5]), "+f"(d[6]), "+f"(d[7]), "+f"(d[8]), "+f"(d[9]), "+f"(d[10]), "+f"(d[11]), "+f"(d[12]), "+f"(d[13]), "+f"(d[14]), "+f"(d[15]), "+f"(d[16]), "+f"(d[17]), "+f"(d[18]), "+f"(d[19]), "+f"(d[20]), "+f"(d[21]), "+f"(d[22]), "+f"(d[23])
    : "l"(descA), "l"(descB), "r"(scaleD));
}
__device__ __forceinline__ void wgmma_rs_n32_t0(float* d, uint32_t a0, uint32_t a1, uint32_t a2, uint32_t a3, uint64_t descB, int scaleD) {
  asm volatile("{\n.reg .pred p;\nsetp.ne.b32 p, %21, 0;\n"
    "wgmma.mma_async.sync.aligned.m64n32k16.f32.bf16.bf16 {%0,%1,%2,%3,%4,%5,%6,%7,%8,%9,%10,%11,%12,%13,%14,%15}, {%16,%17,%18,%19}, %20, p, 1, 1, 0;\n}\n"
    : "+f"(d[0]), "+f"(d[1]), "+f"(d[2]), "+f"(d[3]), "+f"(d[4]), "+f"(d[5]), "+f"(d[6]), "+f"(d[7]), "+f"(d[8]), "+f"(d[9]), "+f"(d[10]), "+f"(d[11]), "+f"(d[12]), "+f"(d[13]), "+f"(d[14]), "+f"(d[15])
    : "r"(a0), "r"(a1), "r"(a2), "r"(a3), "l"(descB), "r"(scaleD));
}

#define PFLA 3
constexpr int L_ = 2048, D_ = 576, F_ = 4608;
constexpr int NFFN = 128, NCTA = 132, NTHR = 384;
constexpr int STG_BYTES = 12288;
constexpr uint32_t S_X = 1024;
constexpr uint32_t S_RING = S_X + 147456;
constexpr uint32_t S_MISC = S_RING + 6 * STG_BYTES;
constexpr uint32_t S_BAR = S_MISC + 8320, S_DSK = S_BAR + 512, S_DUMMY = S_DSK + 256;
constexpr int SMEM_BYTES = S_DUMMY + 256 - 1024;
constexpr uint32_t B_FULL = S_BAR, B_EMPTY = S_BAR + 64, B_X = S_BAR + 128  , B_PFREE = S_BAR + 176, B_BASE = S_BAR + 184  ,
                   B_RAW = S_BAR + 200, B_LN = S_BAR + 208, B_U = S_BAR + 216  , B_KDONE = S_BAR + 232  , B_CDONE = S_BAR + 248  ,
                   B_RDONE = S_BAR + 264  , B_H = S_BAR + 280, B_YDONE = S_BAR + 288, B_PP = S_BAR + 296  , B_GO = S_BAR + 312, B_PUB = S_BAR + 320  , B_R = S_BAR + 344, B_H8 = S_BAR + 352, B_EP = S_BAR + 360;
constexpr uint32_t S_LN = S_RING + 3 * STG_BYTES;
constexpr uint32_t S_U = S_LN + 20480;
__device__ __forceinline__ uint32_t s_w_of(int ch) { return ch < 2 ? S_LN + ch * 8256 : (ch == 2 ? S_X + 8 * 16384 : S_MISC); }
__host__ __device__ constexpr int xslot(int kb) { return kb < 3 ? kb : (kb < 6 ? kb + 1 : (kb == 6 ? 3 : kb)); }

__device__ __nv_bfloat16 g_xt[D_ * L_];
__device__ __nv_bfloat16 g_yt[D_ * L_];
__device__ uint4 g_part[16 * 8 * 3 * 1024];
__device__ uint4 g_acc[16 * 9 * 1024];
__device__ unsigned int g_cnt_acc[16 * 9 * 8];
__device__ unsigned int g_ticket, g_cnt_all, g_cnt_y, g_cnt_ys;
#define TSTAMP(i)
#define TSTAMP1(w, i)

#define CT(i)
#define KT(i)
__device__ __forceinline__ uint32_t smem_u32(const void* p) { return (uint32_t)__cvta_generic_to_shared(p); }
__device__ __forceinline__ void mbar_init(uint32_t bar, uint32_t cnt) { asm volatile("mbarrier.init.shared::cta.b64 [%0], %1;" :: "r"(bar), "r"(cnt)); }
__device__ __forceinline__ void mbar_expect_tx(uint32_t bar, uint32_t bytes) { asm volatile("mbarrier.arrive.expect_tx.shared::cta.b64 _, [%0], %1;" :: "r"(bar), "r"(bytes) : "memory"); }
__device__ __forceinline__ void mbar_arrive(uint32_t bar) { asm volatile("mbarrier.arrive.shared::cta.b64 _, [%0];" :: "r"(bar) : "memory"); }
__device__ __forceinline__ bool mbar_try_wait(uint32_t bar, uint32_t parity) {
  uint32_t ok;
  asm volatile("{\n.reg .pred p;\nmbarrier.try_wait.parity.shared::cta.b64 p, [%1], %2;\nselp.u32 %0, 1, 0, p;\n}\n" : "=r"(ok) : "r"(bar), "r"(parity) : "memory");
  return ok;
}
__device__ __forceinline__ void mbar_wait(uint32_t bar, uint32_t parity) {
  asm volatile("{\n.reg .pred p;\n.reg .u32 c;\nmov.u32 c, 0;\n"
               "WAIT_LOOP:\nmbarrier.try_wait.parity.shared::cta.b64 p, [%0], %1;\nadd.u32 c, c, 1;\n@!p setp.gt.u32 p, c, 1024;\n@!p bra WAIT_LOOP;\n}\n" :: "r"(bar), "r"(parity) : "memory");
}
__device__ __forceinline__ void flag_wait(const unsigned int* f, unsigned int val, bool slow = false) {
  const unsigned int t0 = (unsigned int)clock();
  unsigned int v;
  while (true) {
    asm volatile("ld.relaxed.gpu.global.u32 %0, [%1];" : "=r"(v) : "l"(f) : "memory");
    if (v == val || (unsigned int)clock() - t0 > 0x400000u) break;
    if (slow) __nanosleep(500);
  }
  asm volatile("fence.acq_rel.gpu;" ::: "memory");
}
__device__ __forceinline__ void red_add(unsigned int* p) { asm volatile("red.relaxed.gpu.global.add.u32 [%0], 1;" :: "l"(p) : "memory"); }
__device__ __forceinline__ void fence_gpu() { asm volatile("fence.acq_rel.gpu;" ::: "memory"); }
__device__ __forceinline__ void fence_async() { asm volatile("fence.proxy.async.global;" ::: "memory"); }
__device__ __forceinline__ void fence_async_smem() { asm volatile("fence.proxy.async.shared::cta;" ::: "memory"); }
__device__ __forceinline__ unsigned int cur_epoch() { mbar_wait(B_EP, 0); unsigned int v; asm volatile("ld.shared.b32 %0, [%1];" : "=r"(v) : "r"(S_DSK + 196) : "memory"); return v; }
__device__ __forceinline__ void tma2d(uint32_t dst, const CUtensorMap* tm, int c0, int c1, uint32_t bar) {
  asm volatile("cp.async.bulk.tensor.2d.shared::cluster.global.mbarrier::complete_tx::bytes [%0], [%1, {%3, %4}], [%2];" :: "r"(dst), "l"(tm), "r"(bar), "r"(c0), "r"(c1) : "memory");
}
__device__ __forceinline__ void tma3d(uint32_t dst, const CUtensorMap* tm, int c0, int c1, int c2, uint32_t bar) {
  asm volatile("cp.async.bulk.tensor.3d.shared::cluster.global.mbarrier::complete_tx::bytes [%0], [%1, {%3, %4, %5}], [%2];" :: "r"(dst), "l"(tm), "r"(bar), "r"(c0), "r"(c1), "r"(c2) : "memory");
}
__device__ __forceinline__ void bulk_g2s(uint32_t dst, const void* src, uint32_t bytes, uint32_t bar) {
  asm volatile("cp.async.bulk.shared::cluster.global.mbarrier::complete_tx::bytes [%0], [%1], %2, [%3];" :: "r"(dst), "l"(src), "r"(bytes), "r"(bar) : "memory");
}
__device__ __forceinline__ void prefetch_tmap(const CUtensorMap* tm) { asm volatile("prefetch.tensormap [%0];" :: "l"(tm) : "memory"); }
__device__ __forceinline__ void wg_fence() { asm volatile("wgmma.fence.sync.aligned;" ::: "memory"); }
__device__ __forceinline__ void wg_commit() { asm volatile("wgmma.commit_group.sync.aligned;" ::: "memory"); }
template <int N> __device__ __forceinline__ void wg_wait() { asm volatile("wgmma.wait_group.sync.aligned %0;" :: "n"(N) : "memory"); }
__device__ __forceinline__ void bar_sync(int id, int n) { asm volatile("bar.sync %0, %1;" :: "r"(id), "r"(n) : "memory"); }
__device__ __forceinline__ void bar_arrive(int id, int n) { asm volatile("bar.arrive %0, %1;" :: "r"(id), "r"(n) : "memory"); }
__device__ __forceinline__ uint32_t pack_bf16(float lo, float hi) { uint32_t r; asm("cvt.rn.bf16x2.f32 %0, %1, %2;" : "=r"(r) : "f"(hi), "f"(lo)); return r; }
__device__ __forceinline__ float bf_lo(uint32_t v) { return __uint_as_float(v << 16); }
__device__ __forceinline__ float bf_hi(uint32_t v) { return __uint_as_float(v & 0xFFFF0000u); }
__device__ __forceinline__ float bf_round(float v) { return bf_lo(pack_bf16(v, v)); }
__device__ __forceinline__ uint32_t mul_bf16x2(uint32_t a, uint32_t b) { uint32_t r; asm("mul.rn.bf16x2 %0, %1, %2;" : "=r"(r) : "r"(a), "r"(b)); return r; }
__device__ __forceinline__ uint32_t add_bf16x2(uint32_t a, uint32_t b) { uint32_t r; asm("add.rn.bf16x2 %0, %1, %2;" : "=r"(r) : "r"(a), "r"(b)); return r; }
__device__ __forceinline__ uint32_t sub_bf16x2(uint32_t a, uint32_t b) { uint32_t r; asm("sub.rn.bf16x2 %0, %1, %2;" : "=r"(r) : "r"(a), "r"(b)); return r; }
__device__ __forceinline__ void ldsm_x4(uint32_t addr, uint32_t& r0, uint32_t& r1, uint32_t& r2, uint32_t& r3) {
  asm volatile("ldmatrix.sync.aligned.m8n8.x4.shared.b16 {%0,%1,%2,%3}, [%4];" : "=r"(r0), "=r"(r1), "=r"(r2), "=r"(r3) : "r"(addr) : "memory");
}
__device__ __forceinline__ void ldsm_x4t(uint32_t addr, uint32_t& r0, uint32_t& r1, uint32_t& r2, uint32_t& r3) {
  asm volatile("ldmatrix.sync.aligned.m8n8.x4.trans.shared.b16 {%0,%1,%2,%3}, [%4];" : "=r"(r0), "=r"(r1), "=r"(r2), "=r"(r3) : "r"(addr) : "memory");
}
__device__ __forceinline__ float silu_f(float g) {
  float e; asm("ex2.approx.ftz.f32 %0, %1;" : "=f"(e) : "f"(g * -1.4426950408889634f));
  float r; asm("rcp.approx.ftz.f32 %0, %1;" : "=f"(r) : "f"(1.0f + e));
  return g * r;
}
__device__ __forceinline__ void sts128(uint32_t addr, uint32_t a, uint32_t b, uint32_t c, uint32_t d) { asm volatile("st.shared.v4.b32 [%0], {%1,%2,%3,%4};" :: "r"(addr), "r"(a), "r"(b), "r"(c), "r"(d) : "memory"); }
__device__ __forceinline__ void sts64(uint32_t addr, uint32_t a, uint32_t b) { asm volatile("st.shared.v2.b32 [%0], {%1,%2};" :: "r"(addr), "r"(a), "r"(b) : "memory"); }
__device__ __forceinline__ void sts32(uint32_t addr, uint32_t a) { asm volatile("st.shared.b32 [%0], %1;" :: "r"(addr), "r"(a) : "memory"); }
__device__ __forceinline__ void lds128(uint32_t addr, uint32_t& a, uint32_t& b, uint32_t& c, uint32_t& d) { asm volatile("ld.shared.v4.b32 {%0,%1,%2,%3}, [%4];" : "=r"(a), "=r"(b), "=r"(c), "=r"(d) : "r"(addr) : "memory"); }
__device__ __forceinline__ void lds64(uint32_t addr, uint32_t& a, uint32_t& b) { asm volatile("ld.shared.v2.b32 {%0,%1}, [%2];" : "=r"(a), "=r"(b) : "r"(addr) : "memory"); }
__device__ __forceinline__ uint32_t lds32(uint32_t addr) { uint32_t a; asm volatile("ld.shared.b32 %0, [%1];" : "=r"(a) : "r"(addr) : "memory"); return a; }
__device__ __forceinline__ float ldsf(uint32_t addr) { float a; asm volatile("ld.shared.f32 %0, [%1];" : "=f"(a) : "r"(addr) : "memory"); return a; }
__device__ __forceinline__ uint32_t opaque(uint32_t v) { uint32_t r; asm volatile("mov.b32 %0, %1;" : "=r"(r) : "r"(v)); return r; }
__device__ __forceinline__ void cp_async16(uint32_t dst, const void* src) { asm volatile("cp.async.cg.shared.global [%0], [%1], 16;" :: "r"(dst), "l"(src) : "memory"); }
__device__ __forceinline__ void cp_commit() { asm volatile("cp.async.commit_group;" ::: "memory"); }
template <int N> __device__ __forceinline__ void cp_wait() { asm volatile("cp.async.wait_group %0;" :: "n"(N) : "memory"); }
__device__ __forceinline__ void st_relaxed_v4(uint4* p, uint32_t a, uint32_t b, uint32_t c, uint32_t d) {
  asm volatile("st.relaxed.gpu.global.v4.b32 [%0], {%1,%2,%3,%4};" :: "l"(p), "r"(a), "r"(b), "r"(c), "r"(d) : "memory");
}
__device__ __forceinline__ void ld_relaxed_v4(const uint4* p, uint32_t& a, uint32_t& b, uint32_t& c, uint32_t& d) {
  asm volatile("ld.relaxed.gpu.global.v4.b32 {%0,%1,%2,%3}, [%4];" : "=r"(a), "=r"(b), "=r"(c), "=r"(d) : "l"(p) : "memory");
}
__device__ __forceinline__ bool tag_bad(uint32_t a, uint32_t b, uint32_t c, uint32_t d, uint32_t tag) { return (((a ^ tag) | (b ^ tag) | (c ^ tag) | (d ^ tag)) & 1u) != 0; }
__device__ __forceinline__ void poll_v4(const uint4* p, uint32_t& a, uint32_t& b, uint32_t& c, uint32_t& d, uint32_t tag) {
  int it = 0;
  do { ld_relaxed_v4(p, a, b, c, d); } while (tag_bad(a, b, c, d, tag) && ++it < 4096);
}
__device__ __forceinline__ void add_vec(float* f, uint32_t v0, uint32_t v1, uint32_t v2, uint32_t v3) {
  f[0] += bf_lo(v0); f[1] += bf_hi(v0); f[2] += bf_lo(v1); f[3] += bf_hi(v1); f[4] += bf_lo(v2); f[5] += bf_hi(v2); f[6] += bf_lo(v3); f[7] += bf_hi(v3);
}

struct cplx { float re, im; };
__device__ __forceinline__ cplx cmul(cplx a, cplx b) { return {fmaf(a.re, b.re, -a.im * b.im), fmaf(a.re, b.im, a.im * b.re)}; }
__device__ __forceinline__ cplx cexp_f(float ar, float ai) {
  float mag; asm("ex2.approx.f32 %0, %1;" : "=f"(mag) : "f"(ar * 1.4426950408889634f));
  const float k = rintf(ai * 0.15915494309189535f);
  float r = fmaf(ai, 0.15915494309189535f, -k);
  r = fmaf(ai, 6.4206383e-9f, r);
  r *= 6.283185307179586f;
  float sn, cs; asm("sin.approx.f32 %0, %1;" : "=f"(sn) : "f"(r)); asm("cos.approx.f32 %0, %1;" : "=f"(cs) : "f"(r));
  return {mag * cs, mag * sn};
}
__device__ __forceinline__ float bf2f(__nv_bfloat16 v) { return __bfloat162float(v); }

constexpr int KG_B = 32768, KG_TAB = 2688;

struct SsmParams { const __nv_bfloat16 *are, *aim, *bre, *bim, *cre, *cim, *logdt; };
struct ModeRaw { uint32_t are, aim, bre, bim, cre, cim; __nv_bfloat16 ldt; };
__device__ __forceinline__ ModeRaw load_mode(const SsmParams& p, int d, int t128) {
  const int o = d * 64 + t128;
  auto ld = [&](const __nv_bfloat16* b) { return __ldg((const uint32_t*)b + o); };
  return {ld(p.are), ld(p.aim), ld(p.bre), ld(p.bim), ld(p.cre), ld(p.cim), __ldg(p.logdt + d + (t128 >> 6))};
}

__device__ __forceinline__ void layer_norm16(int row0, int tid_);
__device__ __forceinline__ void kgen_powers(const ModeRaw& mr, int wg, int t128_, int row0, bool g_first) {
  const int t128 = opaque(t128_);
  const uint32_t scr = S_X + wg * 65536;
  const int warp = t128 >> 5, lane = t128 & 31;
  cplx cb[2], z1[2], zq[2];
  const float dt = bf_round(expf(bf2f(mr.ldt)));
  #pragma unroll
  for (int c = 0; c < 2; c++) {
    auto f = [&](uint32_t v) { return c ? bf_hi(v) : bf_lo(v); };
    const float ar = dt * f(mr.are), ai = dt * f(mr.aim);
    cb[c] = cmul({f(mr.cre), f(mr.cim)}, {dt * f(mr.bre), dt * f(mr.bim)});
    z1[c] = cexp_f(ar, ai); zq[c] = cexp_f(ar * 256.f, ai * 256.f);
  }
  KT(12);
  uint32_t ad[8];
  #pragma unroll
  for (int i = 0; i < 8; i++) ad[i] = scr + KG_B + ((warp & 1) * 2 + (lane >> 4)) * 6144 + (warp >> 1) * 3072 + (lane & 1) * 8 + ((((lane >> 1) & 7) ^ i) << 4);
  cplx z2[2];
  {
    auto put = [&](int b, const cplx* v) { sts64(ad[b & 7] + b * 128, pack_bf16(v[0].re, -v[0].im), pack_bf16(v[1].re, -v[1].im)); };
    cplx e[2], o[2], h[2], h0[2], h4[2];
    #pragma unroll
    for (int c = 0; c < 2; c++) { z2[c] = cmul(z1[c], z1[c]); e[c] = cb[c]; o[c] = cmul(cb[c], z1[c]); }
    #pragma unroll
    for (int i = 0; i < 4; i++) {
      put(2 * i, e); put(2 * i + 1, o);
      #pragma unroll
      for (int c = 0; c < 2; c++) {
        h[c] = cmul(e[c], zq[c]);
        if (i == 0) h0[c] = h[c];
        if (i == 2) h4[c] = h[c];
        if (i < 3) { e[c] = cmul(e[c], z2[c]); o[c] = cmul(o[c], z2[c]); }
      }
      put(8 + i, h);
    }
    #pragma unroll
    for (int i = 0; i < 7; i++) {
      #pragma unroll
      for (int c = 0; c < 2; c++) { h0[c] = cmul(h0[c], zq[c]); if (i < 2) h4[c] = cmul(h4[c], zq[c]); }
      put(i < 2 ? 12 + 2 * i : 14 + i, h0);
      if (i < 2) put(13 + 2 * i, h4);
    }
  }
  KT(13);
  if (row0 >= 0) layer_norm16(row0, wg * 128 + t128);
  {
    #pragma unroll
    for (int i = 0; i < 8; i++) ad[i] += ((warp & 1) * 2 + (lane >> 4)) * 2048 + (warp >> 1) * 1024 - KG_B;
    cplx y[2][2], z16[2];
    #pragma unroll
    for (int c = 0; c < 2; c++) { const cplx z4 = cmul(z2[c], z2[c]); y[0][c] = {1.f, 0.f}; y[1][c] = cmul(z4, z4); z16[c] = cmul(y[1][c], y[1][c]); }
    #pragma unroll 1
    for (int jo = 0; jo < 4096; jo += 1024) {
      #pragma unroll
      for (int jj = 0; jj < 8; jj++) {
        sts64(ad[jj] + jo + jj * 128, pack_bf16(y[jj & 1][0].re, y[jj & 1][0].im), pack_bf16(y[jj & 1][1].re, y[jj & 1][1].im));
        #pragma unroll
        for (int c = 0; c < 2; c++) y[jj & 1][c] = cmul(y[jj & 1][c], z16[c]);
      }
    }
  }
  KT(14);
  fence_async_smem();
}
__device__ __forceinline__ void kgen_finish(int wg, int t128_, bool wait_ln, bool g_first) {
  const int t128 = opaque(t128_);
  const uint32_t scr = S_X + wg * 65536;
  const int warp = t128 >> 5, lane = t128 & 31;
  bar_sync(2 + wg, 128);
  KT(15);
  float dd[24];
  {
    wg_fence();
    const uint64_t da = ((uint64_t)0x40000040u << 32) | opaque((scr >> 4) | 0x10000u), db = da + KG_B / 16;
    #pragma unroll
    for (int ks = 0; ks < 16; ks++) wgmma_ss_n48_t0(dd, da + (ks >> 2) * 512 + (ks & 3) * 2, db + (ks >> 2) * 384 + (ks & 3) * 2, ks != 0);
    wg_commit();
    wg_wait<0>();
  }
  KT(16);
  bar_sync(2 + wg, 128);
  {
    const int g = lane >> 2, q = lane & 3, hi = warp >> 1;
    const uint32_t tb = scr + hi * KG_TAB;
    #pragma unroll
    for (int rr = 0; rr < 2; rr++) {
      const int jj = (warp & 1) * 16 + g + rr * 8;
      float v[6];
      #pragma unroll
      for (int b = 0; b < 3; b++) { v[b * 2] = hi ? dd[12 + b * 4 + rr * 2] : dd[b * 4 + rr * 2]; v[b * 2 + 1] = hi ? dd[12 + b * 4 + rr * 2 + 1] : dd[b * 4 + rr * 2 + 1]; }
      sts64(tb + (8 * jj + 2 * q) * 4, __float_as_uint(v[0]), __float_as_uint(v[1]));
      sts64(tb + (q < 2 ? 256 + 4 * jj + 2 * q : 256 + 64 * q + 2 * jj) * 4, __float_as_uint(v[2]), __float_as_uint(v[3]));
      if (q < 2) { sts32(tb + (512 + 64 * q + jj) * 4, __float_as_uint(v[4])); sts32(tb + (544 + 64 * q + jj) * 4, __float_as_uint(v[5])); }
      else if (q == 2 && jj == 0) sts32(tb + 640 * 4, __float_as_uint(v[4]));
    }
  }
  KT(17);
  if (wait_ln) mbar_wait(B_LN, 0);
  bar_sync(2 + wg, 128);
  #pragma unroll 1
  for (int c = 0; c < 2; c++) {
    const uint32_t t0 = scr + c * KG_TAB, wp = s_w_of(wg * 2 + c) + 64 + t128 * 16;
    const int t = t128;
    float k0, k1, k2, k3, kp;
    if (warp < 2) {
      uint32_t a0, a1, a2, a3; lds128(t0 + 16 * t, a0, a1, a2, a3);
      k0 = __uint_as_float(a0); k1 = __uint_as_float(a1); k2 = __uint_as_float(a2); k3 = __uint_as_float(a3);
      kp = ldsf(t0 + 16 * t - (t ? 4 : 0)); if (t == 0) kp = 0.f;
    } else {
      uint32_t a0, a1; lds64(t0 + (128 + 2 * t) * 4, a0, a1);
      k0 = k1 = __uint_as_float(a0); k2 = __uint_as_float(a1); k3 = ldsf(t0 + (130 + 2 * t) * 4);
      kp = ldsf(t0 + (t == 64 ? 255 : 128 + 2 * t) * 4);
    }
    const float s0 = ldsf(t0 + (384 + t) * 4), s1 = ldsf(t0 + (385 + t) * 4);
    const int ph = t & 3, b3 = 512 + 2 * (t >> 2);
    const float a0 = ldsf(t0 + (b3 + (ph >> 1)) * 4), c0 = ldsf(t0 + (b3 + ((ph + 1) >> 1)) * 4);
    const float a1 = ldsf(t0 + (b3 + 64 + (ph >> 1)) * 4), c1 = ldsf(t0 + (b3 + 64 + ((ph + 1) >> 1)) * 4);
    sts128(wp, pack_bf16(k0, kp), pack_bf16(k1, k0), pack_bf16(k2, k1), pack_bf16(k3, k2));
    const float m = (t & 1) ? s1 : s0;
    sts128(wp + 2048, pack_bf16(s0, s0), pack_bf16(s0, s0), pack_bf16(m, s0), pack_bf16(s1, m));
    const float f0 = ph == 1 ? a0 : c0, f1 = ph == 1 ? a1 : c1;
    sts128(wp + 4096, pack_bf16(f0, a0), pack_bf16(c0, f0), pack_bf16(c0, c0), pack_bf16(c0, c0));
    sts128(wp + 6144, pack_bf16(f1, a1), pack_bf16(c1, f1), pack_bf16(c1, c1), pack_bf16(c1, c1));
    if (t < 4) sts128(wp - 64, 0, 0, 0, 0);
    if (t < 112) sts128(S_U - 3584 + c * 1792 + t * 16, 0, 0, 0, 0);
  }
}

template <int P> __device__ __forceinline__ void conv_step(float* acc, const uint32_t* fr, uint32_t db) {
  uint32_t lo; asm volatile("sub.u32 %0, %1, %2;" : "=r"(lo) : "r"(db), "n"(32 * P - 256 * 3));
  uint64_t d = ((uint64_t)0x40000040u << 32) | lo;
  #pragma unroll
  for (int sg = 3; sg >= P / 8; sg--) wgmma_rs_n32_t0(acc + 16 * sg, fr[0], fr[1], fr[2], fr[3], d - 256 * (3 - sg), P != 0);
}
template <int I, int I1> struct ConvPairs {
  static __device__ __forceinline__ void run(float* acc, const uint32_t* fr, uint32_t db) {
    conv_step<I>(acc, fr + I * 4, db); conv_step<31 - I>(acc, fr + (31 - I) * 4, db);
    ConvPairs<I + 1, I1>::run(acc, fr, db);
  }
};
template <int I1> struct ConvPairs<I1, I1> { static __device__ __forceinline__ void run(float*, const uint32_t*, uint32_t) {} };

__device__ __forceinline__ void conv_reduce(uint32_t s_r, int t128, __nv_bfloat16* yrow) {
  #pragma unroll
  for (int h = 0; h < 2; h++) {
    const int cc = t128 + h * 128;
    uint32_t v[4][4];
    #pragma unroll
    for (int b = 0; b < 4; b++) {
      lds128(s_r + b * 4096 + cc * 16, v[b][0], v[b][1], v[b][2], v[b][3]);
      if (h == 0 && b > (cc >> 1)) { v[b][0] = v[b][1] = v[b][2] = v[b][3] = 0; }
    }
    uint32_t o[4];
    #pragma unroll
    for (int e = 0; e < 4; e++) { const uint32_t p = add_bf16x2(v[0][e], v[1][e]), q = add_bf16x2(v[2][e], v[3][e]); o[e] = add_bf16x2(p, q); }
    *(uint4*)(yrow + cc * 8) = make_uint4(o[0], o[1], o[2], o[3]);
  }
}
__device__ __forceinline__ void conv_one(int wg, int c, int t128_, int uphase) {
  const int t128 = opaque(t128_), ch = wg * 2 + c;
  const uint32_t s_w = s_w_of(ch), s_r = S_X + wg * 65536 + 49152;
  const int warp = t128 >> 5, lane = t128 & 31;
  float acc[64];
  uint32_t fr[128];
  const uint32_t wa = s_w + 64 + (warp * 16 + (lane >> 2) - 2 * (lane & 3)) * 4;
  const uint32_t zero = lds32(s_w);
  auto ld = [&](int p) { fr[p * 4] = lds32(wa + p * 256); fr[p * 4 + 1] = lds32(wa + p * 256 + 32); fr[p * 4 + 2] = lds32(wa + p * 256 - 32);
                         asm volatile("xor.b32 %0, %1, %2;" : "=r"(fr[p * 4 + 3]) : "r"(fr[p * 4]), "r"(zero)); };
  const uint32_t db = ((S_U >> 4) | 0x10000u) + ch * 2;
  #pragma unroll
  for (int p = 0; p < 32; p++) ld(p);
  CT(0);
  if (c == 0) mbar_wait(B_U, uphase);
  mbar_wait(B_PP + 8 * wg, wg ? c : c ^ 1);
  CT(1);
  wg_fence();
  ConvPairs<0, 16>::run(acc, fr, db);
  wg_commit();
  if (lane == 0) mbar_arrive(B_PP + 8 - 8 * wg);
  CT(2);
  wg_wait<0>();
  CT(3);
  if (c == 1 && lane == 0) mbar_arrive(B_CDONE);
  bar_sync(2 + wg, 128);
  const int col = 8 * (lane >> 4) + (lane & 7) + warp;
  const uint32_t ra = s_r + warp * 4096 + (col * 16 + ((lane >> 3) & 1) * 8) * 2;
  #pragma unroll
  for (int v = 0; v < 8; v++)
    asm volatile("stmatrix.sync.aligned.m8n8.x4.trans.shared.b16 [%0], {%1,%2,%3,%4};" :: "r"((v == 7 && col >= 16) ? S_DUMMY : ra + v * 512),
                 "r"(pack_bf16(acc[v * 8], acc[v * 8 + 1])), "r"(pack_bf16(acc[v * 8 + 2], acc[v * 8 + 3])), "r"(pack_bf16(acc[v * 8 + 4], acc[v * 8 + 5])), "r"(pack_bf16(acc[v * 8 + 6], acc[v * 8 + 7])) : "memory");
  bar_sync(2 + wg, 128);
  CT(4);
}

__device__ __forceinline__ void layer_norm16(int row0, int tid_) {
  const int tid = opaque(tid_), row = tid >> 4, l16 = tid & 15;
  const bool g_first = true; (void)g_first;
  const uint32_t ra = S_LN + (l16 >> 3) * 2048 + row * 128 + (((l16 & 7) ^ (row & 7)) << 4);
  uint32_t v[20];
  KT(20);
  mbar_wait(B_RAW, 0);
  KT(21);
  #pragma unroll
  for (int i = 0; i < 4; i++) lds128(ra + i * 4096, v[i * 4], v[i * 4 + 1], v[i * 4 + 2], v[i * 4 + 3]);
  v[16] = v[17] = v[18] = v[19] = 0;
  if (l16 < 8) lds128(ra + 16384, v[16], v[17], v[18], v[19]);
  float s0 = 0.f, s1 = 0.f, q0 = 0.f, q1 = 0.f;
  #pragma unroll
  for (int e = 0; e < 20; e++) { const float lo = bf_lo(v[e]), hi = bf_hi(v[e]); s0 += lo; s1 += hi; q0 = fmaf(lo, lo, q0); q1 = fmaf(hi, hi, q1); }
  float s = s0 + s1, ss = q0 + q1;
  #pragma unroll
  for (int o = 8; o; o >>= 1) { s += __shfl_xor_sync(0xffffffffu, s, o); ss += __shfl_xor_sync(0xffffffffu, ss, o); }
  const float mean = s * (1.f / D_), var = fmaxf(fmaf(-mean, mean, ss * (1.f / D_)), 0.f);
  const uint32_t mb = pack_bf16(mean, mean);
  const float rs = 1.0f / bf_round(sqrtf(bf_round(bf_round(var) + 1e-5f)));
  KT(22);
  #pragma unroll
  for (int e = 0; e < 20; e++) { const uint32_t dd = sub_bf16x2(v[e], mb); v[e] = pack_bf16(bf_lo(dd) * rs, bf_hi(dd) * rs); }
  #pragma unroll
  for (int i = 0; i < 5; i++) if (i < 4 || l16 < 8) sts128(ra + i * 4096, v[i * 4], v[i * 4 + 1], v[i * 4 + 2], v[i * 4 + 3]);
  KT(23);
  bar_sync(4, 256);
  {
    const int warp = tid >> 5, lane = tid & 31, r = lane & 7, e = lane >> 3, tok = (r >> 1) * 4 + (r & 1) + (e & 1) * 2;
    __nv_bfloat16* tp = g_xt + row0 * D_ + (warp * 16 + (lane >> 2)) * 16 + (lane & 3) * 4;
    const uint32_t la = S_LN + (warp >> 2) * 2048 + tok * 128 + ((((warp & 3) * 2 + (e >> 1)) ^ (tok & 7)) << 4);
    uint32_t w[20];
    #pragma unroll
    for (int i = 0; i < 5; i++) if (i < 4 || warp < 4) ldsm_x4t(la + i * 4096, w[i * 4], w[i * 4 + 1], w[i * 4 + 2], w[i * 4 + 3]);
    #pragma unroll
    for (int i = 0; i < 5; i++) if (i < 4 || warp < 4) {
      *(uint2*)(tp + i * 128 * 16) = make_uint2(w[i * 4], w[i * 4 + 1]);
      *(uint2*)(tp + (i * 128 + 8) * 16) = make_uint2(w[i * 4 + 2], w[i * 4 + 3]);
    }
  }
  __syncwarp();
  if ((tid & 31) == 0) mbar_arrive(B_LN);
  KT(24);
}

__device__ __forceinline__ void ssm_phase(const SsmParams& p, ModeRaw mr, int wg, int d0, int npair, int row0, int t128) {
  int d = d0 + wg * 2;
  #pragma unroll 1
  for (int it = 0; it < npair; it++, d += 4) {
    kgen_powers(mr, wg, t128, row0, it == 0);
    kgen_finish(wg, t128, row0 >= 0, it == 0);
    fence_async_smem();
    __syncwarp();
    if ((t128 & 31) == 0) mbar_arrive(B_KDONE + 8 * wg);
    bar_sync(2 + wg, 128);
    if (it == 0) TSTAMP(10);
    #pragma unroll 1
    for (int c = 0; c < 2; c++) { conv_one(wg, c, t128, it & 1); conv_reduce(S_X + wg * 65536 + 49152, opaque(t128), g_yt + (d + c) * L_); if (it == 0 && c == 0) TSTAMP(37); }
    fence_async_smem();
    __syncwarp();
    if ((t128 & 31) == 0) mbar_arrive(B_RDONE + 8 * wg);
    if (it + 1 < npair) { mr = load_mode(p, d + 4, t128); bar_sync(4, 256); }
  }
  if ((t128 & 31) == 0) mbar_arrive(B_YDONE);
}

struct Ring { bool ready; int ts; };
__device__ __forceinline__ void arrive_one(uint32_t bar) {
  asm volatile("{\n.reg .pred p;\nelect.sync _|p, 0xffffffff;\n@p mbarrier.arrive.shared::cta.b64 _, [%0];\n}\n" :: "r"(bar) : "memory");
}

template <int PH, int KB0 = 0, int KB1 = 6, bool FIRST = false, bool LAST = false, class Pre, class Slice>
__device__ __forceinline__ void run_pass(float* acc, uint32_t* a, Ring& r, Pre pre, Slice slice) {
  #pragma unroll
  for (int kb = KB0; kb < KB1; kb++) {
    pre(kb);
    if (!r.ready) mbar_wait(B_FULL + 8 * kb, PH);
    if (r.ts >= 0) TSTAMP(r.ts + kb * 2);
    wg_fence();
    const uint64_t d0 = ((uint64_t)0x40000040u << 32) | ((S_RING + kb * STG_BYTES) >> 4) | (512u << 16);
    #pragma unroll
    for (int kk = 0; kk < 6; kk++)
      wgmma_rs_n64_t1(acc, a[(kb * 6 + kk) * 4 + 0], a[(kb * 6 + kk) * 4 + 1], a[(kb * 6 + kk) * 4 + 2], a[(kb * 6 + kk) * 4 + 3], d0 + kk * 128, (kb | kk) != 0);
    wg_commit();
    if (!LAST) r.ready = mbar_try_wait(B_FULL + 8 * ((kb + 1) % 6), kb == 5 ? PH ^ 1 : PH);
    slice(kb);
    if (r.ts >= 0) TSTAMP(r.ts + kb * 2 + 1);
    if (kb > 0 || !FIRST) {
      wg_wait<1>();
      arrive_one(B_EMPTY + 8 * ((kb + 5) % 6));
    }
  }
}

struct CtaId { int m, j; };
__device__ __forceinline__ CtaId cta_id() {
  int bx; asm volatile("mov.u32 %0, %%ctaid.x;" : "=r"(bx));
  bx = __shfl_sync(0xffffffffu, bx, 0);
  return {((bx >> 5) << 2) + ((bx >> 2) & 3), (((bx >> 4) & 1) << 2) + (bx & 3)};
}
__device__ __forceinline__ CtaId cta_id_lane() {
  int bx; asm volatile("mov.u32 %0, %%ctaid.x;" : "=r"(bx));
  return {((bx >> 5) << 2) + ((bx >> 2) & 3), (((bx >> 4) & 1) << 2) + (bx & 3)};
}
struct Maps { CUtensorMap xraw3, x2, xt, xt64, xt8, yt, w1, w3, w2, x8, yt8; };

__global__ void __launch_bounds__(NTHR, 1) k_main(const __grid_constant__ Maps tm, const SsmParams sp, const __nv_bfloat16* __restrict__ dskip,
                                                   __nv_bfloat16* __restrict__ out) {
  extern __shared__ unsigned char smem_raw[];
  const int tid = threadIdx.x, wg = __shfl_sync(0xffffffffu, tid >> 7, 0);
  const int bx = blockIdx.x;
  const bool ffn = bx < NFFN;
  const int m = ((bx >> 5) << 2) + ((bx >> 2) & 3), j = (((bx >> 4) & 1) << 2) + (bx & 3);
  const int d0 = ffn ? bx * 4 : 512 + (bx - NFFN) * 16, npair = ffn ? 1 : 4;
  if (smem_u32(smem_raw) != S_X) return;
  TSTAMP(0);
  if (wg == 2) {
    unsigned int ticket = 0;
    if (tid == 352) ticket = atomicAdd(&g_ticket, 1);
  if (tid == 256) {
    mbar_init(B_RAW, 1);
    asm volatile("fence.mbarrier_init.release.cluster;" ::: "memory");
    if (ffn) { mbar_expect_tx(B_RAW, 18432); tma3d(S_LN, &tm.xraw3, 0, m * 128 + j * 16, 0, B_RAW); }
  } else if (tid == 352) {
    for (int i = 0; i < 6; i++) { mbar_init(B_FULL + 8 * i, 1); mbar_init(B_EMPTY + 8 * i, 8); }
    asm volatile("fence.mbarrier_init.release.cluster;" ::: "memory");
  } else if (tid == 288) {
    for (int i = 0; i < 5; i++) mbar_init(B_X + 8 * i, 1);
    mbar_init(B_EP, 1); mbar_init(B_PFREE, 8); mbar_init(B_GO, 1); mbar_init(B_R, 1); mbar_init(B_H8, 1); mbar_init(B_PUB, 8); mbar_init(B_PUB + 8, 8); mbar_init(B_PUB + 16, 8); mbar_init(B_BASE, 2); mbar_init(B_LN, 8); mbar_init(B_H, 1); mbar_init(B_YDONE, 8);
    mbar_init(B_U, 1); mbar_init(B_CDONE, 8);
    for (int i = 0; i < 2; i++) { mbar_init(B_KDONE + 8 * i, 4); mbar_init(B_PP + 8 * i, 4); mbar_init(B_RDONE + 8 * i, 4); }
    asm volatile("fence.mbarrier_init.release.cluster;" ::: "memory");
  } else if (tid == 320) {
    prefetch_tmap(&tm.xt); prefetch_tmap(&tm.w1); prefetch_tmap(&tm.xt64); prefetch_tmap(&tm.w3);
  }
    bar_sync(0, NTHR);
    asm volatile("setmaxnreg.dec.sync.aligned.u32 24;");
    const int pw = (tid >> 5) & 3, lane = tid & 31;
    if (pw == 0) {
      if (lane == 0) {
        auto wcoord = [&](int p, const CUtensorMap*& t, int& c0, int& c1) {
          if (p < 18) { t = (p & 1) ? &tm.w3 : &tm.w1; c0 = j * 576 + (p >> 1) * 64; c1 = 0; }
          else { const int s = p - 18; t = &tm.w2; c0 = (s == 0 ? 8 : ((j + s) & 7)) * 64; c1 = j * 576; }
        };
        auto l2pf = [&](int p) {
          const int kb = (m - p * 6) & 15;
          if (kb < 6 && p < 27) { const CUtensorMap* t; int c0, c1; wcoord(p, t, c0, c1);
            asm volatile("cp.async.bulk.prefetch.tensor.2d.L2.global [%0, {%1, %2}];" :: "l"(t), "r"(c0), "r"(c1 + kb * 96) : "memory"); }
        };
        auto wload = [&](int p, int kb0, int kb1) {
          const CUtensorMap* t; int c0, c1; wcoord(p, t, c0, c1);
          #pragma unroll 1
          for (int kb = kb0; kb < kb1; kb++) {
            mbar_expect_tx(B_FULL + 8 * kb, STG_BYTES);
            tma2d(S_RING + kb * STG_BYTES, t, c0, c1 + kb * 96, B_FULL + 8 * kb);
          }
        };
        const unsigned int epoch = cur_epoch();
        if (ffn) {
          mbar_wait(B_RAW, 0);
          wload(0, 0, 3);
          #pragma unroll 1
          for (int p = 0; p <= PFLA; p++) l2pf(p);
        }
        #pragma unroll 1
        for (int it = 0; it < 8192; it++) { unsigned int v; asm volatile("ld.acquire.gpu.global.u32 %0, [%1];" : "=r"(v) : "l"(&g_cnt_all) : "memory"); if (v == epoch * NFFN) break; }
        fence_async();
        TSTAMP1(2, 1);
        #pragma unroll 1
        for (int it = 0; it < npair; it++) {
          if (it > 0) mbar_wait(B_CDONE, (it - 1) & 1);
          mbar_expect_tx(B_U, 16384);
          tma2d(S_U, &tm.xt, (d0 + it * 4) * 16, 0, B_U);
        }
        if (ffn) {
          #pragma unroll 1
          for (int w = 0; w < 2; w++) {
            mbar_wait(B_KDONE + 8 * w, 0);
            mbar_expect_tx(B_X + 8 * w, 3 * 16384);
            #pragma unroll 1
            for (int q = 0; q < 3; q++) tma3d(S_X + w * 65536 + q * 16384, &tm.xt64, 0, (w * 3 + q) * 16, m * 8, B_X + 8 * w);
          }
          mbar_wait(B_CDONE, 0);
          wload(0, 3, 6);
          #pragma unroll 1
          for (int w = 0; w < 3; w++) {
            if (w > 0) mbar_wait(B_RDONE - 8 + 8 * w, 0);
            const uint32_t bar = B_X + (w ? 8 + 8 * w : 32);
            mbar_expect_tx(bar, 16384); tma3d(S_X + (w ? 4 * w - 1 : 8) * 16384, &tm.xt64, 0, w ? 80 + 16 * w : 128, m * 8, bar);
          }
          #pragma unroll 1
          for (int p = 1; p < 27; p++) {
            const CUtensorMap* t; int c0, c1; wcoord(p, t, c0, c1);
            #pragma unroll
            for (int kb = 0; kb < 6; kb++) {
              mbar_wait(B_EMPTY + 8 * kb, (p - 1) & 1);
              mbar_expect_tx(B_FULL + 8 * kb, STG_BYTES);
              tma2d(S_RING + kb * STG_BYTES, t, c0, c1 + kb * 96, B_FULL + 8 * kb);
            }
            l2pf(p + PFLA);
          }
        }
      }
      __syncwarp();
    } else {
      const int hw = pw - 1;
      if (tid == 352) { sts32(S_DSK + 196, ticket / NCTA + 1); mbar_arrive(B_EP); }
      __syncwarp();
      if (hw == 0) {
        const unsigned int epoch = cur_epoch();
        if (ffn) { const uint32_t* dp = (const uint32_t*)dskip; sts32(S_DSK + lane * 4, __ldg(dp + j * 32 + (lane & 24) + ((lane >> 1) & 3) + (lane & 1) * 4)); if (lane < 4) sts32(S_DSK + 128 + lane * 4, __ldg(dp + 256 + j * 4 + lane)); }
        if (ffn && lane == 0) { mbar_wait(B_LN, 0); TSTAMP1(2, 2); fence_gpu(); red_add(&g_cnt_all); TSTAMP1(2, 3); }
        __syncwarp();
        mbar_wait(B_CDONE, 0);
        if (ffn) {
          uint4* za = g_acc + (m * 9 + j) * 1024 + lane;
          #pragma unroll 1
          for (int i = 0; i < 32; i++) za[i * 32] = make_uint4(0, 0, 0, 0);
          za = g_acc + (m * 9 + 8) * 1024 + j * 128 + lane;
          #pragma unroll 1
          for (int i = 0; i < 4; i++) za[i * 32] = make_uint4(0, 0, 0, 0);
        }
        __syncwarp();
        if (lane == 0) {
          mbar_wait(B_YDONE, 0);
          fence_gpu(); red_add(ffn ? &g_cnt_y : &g_cnt_ys);
          if (ffn) {
            prefetch_tmap(&tm.x2); prefetch_tmap(&tm.yt); prefetch_tmap(&tm.x8); prefetch_tmap(&tm.xt8); prefetch_tmap(&tm.yt8); prefetch_tmap(&tm.w2);
            flag_wait(&g_cnt_y, epoch * NFFN, true); fence_async();
            mbar_arrive(B_GO);
            mbar_wait(B_PFREE, 0);
            mbar_expect_tx(B_H, 49152);
            tma2d(S_X + 2 * 16384, &tm.x2, j * 64, m * 128, B_H); tma3d(S_X + 3 * 16384, &tm.xt64, 0, j * 16, m * 8, B_H);
            tma2d(S_X + 4 * 16384, &tm.yt, m * 128, j * 64, B_H); tma2d(S_X + 4 * 16384 + 8192, &tm.yt, m * 128 + 64, j * 64, B_H);
            TSTAMP1(2, 4);
            #pragma unroll 1
            for (int k = 0; k < 3; k++) {
              mbar_wait(B_PUB + 8 * k, 0);
              fence_gpu();
              red_add(&g_cnt_acc[(m * 9 + (k ? (j + 2 * k) & 7 : 8)) * 8]);
              if (k < 2) red_add(&g_cnt_acc[(m * 9 + ((j + 2 * k + 1) & 7)) * 8]);
              TSTAMP1(2, 8 + k);
            }
          }
        }
        __syncwarp();
      }
      if (ffn) {
        if (hw > 0) {
          mbar_wait(B_H, 0);
          #pragma unroll 1
          for (int k = hw - 1; k < 32; k += 2) {
            const uint32_t ln = opaque(lane), r7 = ln & 7, dl = (ln >> 4) * 8 + r7, hf = (k >> 4) * 8192, i = (k >> 2) & 3, wp = k & 3;
            uint32_t x[4], n[4], y[4], k0, k1;
            ldsm_x4t(S_X + 3 * 16384 + hf + wp * 2048 + (i * 4 + (dl >> 2)) * 128 + ((((ln & 3) * 2 + ((ln >> 3) & 1)) ^ ((i * 4 + (dl >> 2)) & 7)) << 4), n[0], n[1], n[2], n[3]);
            ldsm_x4t(S_X + 4 * 16384 + hf + i * 2048 + dl * 128 + (((2 * wp + ((ln >> 3) & 1)) ^ r7) << 4), y[0], y[1], y[2], y[3]);
            ldsm_x4(S_X + 2 * 16384 + hf + wp * 2048 + (ln & 15) * 128 + (((2 * i + (ln >> 4)) ^ r7) << 4), x[0], x[1], x[2], x[3]);
            lds64(S_DSK + i * 32 + (ln & 3) * 8, k0, k1);
            sts128(S_X + 7 * 16384 + k * 512 + ln * 16, add_bf16x2(x[0], add_bf16x2(y[0], mul_bf16x2(n[0], k0))), add_bf16x2(x[1], add_bf16x2(y[1], mul_bf16x2(n[1], k0))),
                   add_bf16x2(x[2], add_bf16x2(y[2], mul_bf16x2(n[2], k1))), add_bf16x2(x[3], add_bf16x2(y[3], mul_bf16x2(n[3], k1))));
          }
          __syncwarp();
          if (lane == 0) {
            mbar_arrive(B_BASE);
            TSTAMP1(2, 5 + hw);
            const CtaId id = cta_id_lane();
            const unsigned int epoch = cur_epoch();
            if (hw == 1) {
              flag_wait(&g_cnt_acc[(id.m * 9 + id.j) * 8], epoch * 4, true); fence_async();
              mbar_expect_tx(B_R, 16384); bulk_g2s(S_X + 6 * 16384, g_acc + (id.m * 9 + id.j) * 1024, 16384, B_R);
              TSTAMP1(2, 12);
            } else {
              flag_wait(&g_cnt_ys, epoch * (NCTA - NFFN), true);
              flag_wait(&g_cnt_acc[(id.m * 9 + 8) * 8], epoch * 8, true); fence_async();
              mbar_expect_tx(B_H8, 8192);
              tma2d(S_X + 8 * 16384, &tm.x8, 512 + id.j * 8, id.m * 128, B_H8); tma3d(S_X + 8 * 16384 + 2048, &tm.xt8, 0, 128 + id.j * 2, id.m * 8, B_H8);
              tma2d(S_X + 8 * 16384 + 4096, &tm.yt8, id.m * 128, 512 + id.j * 8, B_H8); tma2d(S_X + 8 * 16384 + 5120, &tm.yt8, id.m * 128 + 64, 512 + id.j * 8, B_H8);
              bulk_g2s(S_X + 8 * 16384 + 6144, g_acc + (id.m * 9 + 8) * 1024 + id.j * 128, 2048, B_H8);
            }
          }
          __syncwarp();
          if (hw == 2) {
            mbar_wait(B_H8, 0);
            #pragma unroll 1
            for (int k = 0; k < 8; k++) {
              const CtaId id = cta_id();
              const uint32_t ln = opaque(lane);
              uint32_t x0, x1, n0, n1, y0, y1, v0, v1;
              asm volatile("ldmatrix.sync.aligned.m8n8.x2.shared.b16 {%0,%1}, [%2];" : "=r"(x0), "=r"(x1) : "r"(S_X + 8 * 16384 + (k * 16 + (ln & 15)) * 16) : "memory");
              ldsm_x4t((ln & 16) ? S_X + 8 * 16384 + 4096 + (k >> 2) * 1024 + (ln & 7) * 128 + ((((k & 3) * 2 + ((ln >> 3) & 1)) ^ (ln & 7)) << 4)
                                 : S_X + 8 * 16384 + 2048 + (k * 2 + ((ln >> 2) & 1)) * 128 + ((((ln & 3) * 2 + ((ln >> 3) & 1)) ^ ((k * 2 + ((ln >> 2) & 1)) & 7)) << 4), n0, n1, y0, y1);
              const uint32_t k0 = lds32(S_DSK + 128 + (ln & 3) * 4);
              lds64(S_X + 8 * 16384 + 6144 + k * 256 + ln * 8, v0, v1);
              __nv_bfloat16* op = out + ((id.m * 128 + k * 16) * D_ + 512 + id.j * 8) + (ln >> 2) * D_ + (ln & 3) * 2;
              *(uint32_t*)op = add_bf16x2(add_bf16x2(x0, add_bf16x2(y0, mul_bf16x2(n0, k0))), v0);
              *(uint32_t*)(op + 8 * D_) = add_bf16x2(add_bf16x2(x1, add_bf16x2(y1, mul_bf16x2(n1, k0))), v1);
            }
            if (lane == 0) TSTAMP1(2, 13);
          }
        }
      }
    }
  } else {
    const ModeRaw mr0 = load_mode(sp, d0 + wg * 2, tid & 127);
    bar_sync(0, NTHR);
    asm volatile("setmaxnreg.inc.sync.aligned.u32 240;");
    const int t128 = tid & 127, warp = t128 >> 5, lane = tid & 31;
    { const bool g_first = true; (void)g_first; KT(19); }
    ssm_phase(sp, mr0, wg, d0, npair, ffn ? m * 128 + j * 16 : -1, t128);
    TSTAMP(9);
    if (ffn) {
    uint32_t a[144];
    float accG[32], accU[32];
    Ring r{false, -1};
    const uint32_t park = S_X + wg * 8192 + t128 * 16;
    auto nop = [](int) {};
    auto silu_slice = [&](int kb, int t) {
      if (kb >= 1 && kb <= 4) {
        const int i0 = (kb - 1) * 8;
        sts128(park + t * 16384 + (kb - 1) * 2048, pack_bf16(silu_f(accG[i0]), silu_f(accG[i0 + 1])), pack_bf16(silu_f(accG[i0 + 2]), silu_f(accG[i0 + 3])),
               pack_bf16(accG[i0 + 4], accG[i0 + 5]), pack_bf16(accG[i0 + 6], accG[i0 + 7]));
      }
    };
    auto mul_unit = [&](int i, int t, uint32_t& h0, uint32_t& h1, uint32_t& h2, uint32_t& h3) {
      uint32_t s0, s1, g2, g3; const int i0 = i * 8;
      lds128(park + t * 16384 + i * 2048, s0, s1, g2, g3);
      h0 = mul_bf16x2(s0, pack_bf16(accU[i0], accU[i0 + 1])); h1 = mul_bf16x2(s1, pack_bf16(accU[i0 + 2], accU[i0 + 3]));
      h2 = mul_bf16x2(pack_bf16(silu_f(bf_lo(g2)), silu_f(bf_hi(g2))), pack_bf16(accU[i0 + 4], accU[i0 + 5]));
      h3 = mul_bf16x2(pack_bf16(silu_f(bf_lo(g3)), silu_f(bf_hi(g3))), pack_bf16(accU[i0 + 6], accU[i0 + 7]));
    };
    {
      const uint32_t xrow = (lane >> 4) * 2 + ((lane >> 2) & 1);
      const uint32_t rbase = S_X + wg * 8192 + warp * 2048 + xrow * 128 + ((((lane & 3) * 2 + ((lane >> 3) & 1)) ^ xrow) << 4);
      auto ldx = [&](int kb) {
          if (kb == 0) mbar_wait(B_X, 0);
          if (kb == 2) mbar_wait(B_X + 8, 0);
          if (kb == 4) { mbar_wait(B_X + 16, 0); mbar_wait(B_X + 24, 0); }
          if (kb == 5) mbar_wait(B_X + 32, 0);
          #pragma unroll
          for (int kk = 0; kk < 6; kk++) {
            const int ks = kb * 6 + kk;
            ldsm_x4t((rbase ^ ((ks & 1) * 64)) + xslot(ks >> 2) * 16384 + (ks & 3) * 512, a[ks * 4 + 0], a[ks * 4 + 1], a[ks * 4 + 2], a[ks * 4 + 3]);
          }
          if (kb == 0) TSTAMP(1);
        };
      run_pass<0, 0, 5, true>(accG, a, r, ldx, nop);
      ldx(5);
    }
    bar_sync(2 + wg, 128);
    auto reload = [&](int grp, int on) {
      #pragma unroll
      for (int i = 0; i < 6; i++) {
        const int q = grp * 6 + i;
        if (q < 32) asm volatile("{\n.reg .pred p;\nsetp.ne.b32 p, %5, 0;\n@p ld.shared.v4.b32 {%0,%1,%2,%3}, [%4];\n}\n"
                                 : "+r"(a[q * 4]), "+r"(a[q * 4 + 1]), "+r"(a[q * 4 + 2]), "+r"(a[q * 4 + 3]) : "r"(park + (q >> 2) * 16384 + (q & 3) * 2048), "r"(on) : "memory");
      }
    };
    #pragma unroll 1
    for (int t = 0; t < 9; t++) {
      run_pass<0, 5, 6>(accG, a, r, nop, nop);
      run_pass<1>(accU, a, r, nop, [&](int kb) { silu_slice(kb, t); if (kb >= 2) reload(kb - 2, t == 8); });
      run_pass<0, 0, 5>(accG, a, r, nop, [&](int kb) {
        if (kb <= 1) reload(4 + kb, t == 8);
        if (kb >= 1) {
          uint32_t h0, h1, h2, h3; mul_unit(kb - 1, t, h0, h1, h2, h3);
          sts128(park + t * 16384 + (kb - 1) * 2048, h0, h1, h2, h3);
          asm volatile("{\n.reg .pred p;\nsetp.ne.b32 p, %8, 0;\n@p mov.b32 %0, %4;\n@p mov.b32 %1, %5;\n@p mov.b32 %2, %6;\n@p mov.b32 %3, %7;\n}\n"
                       : "+r"(a[124 + kb * 4]), "+r"(a[125 + kb * 4]), "+r"(a[126 + kb * 4]), "+r"(a[127 + kb * 4]) : "r"(h0), "r"(h1), "r"(h2), "r"(h3), "r"((int)(t == 8)));
        } });
      r.ts = -1;
      if (t == 0) TSTAMP(2);
      if (t == 7) TSTAMP(3);
    }
    TSTAMP(4);
    fence_async_smem(); __syncwarp(); arrive_one(B_PFREE);
    const uint32_t tag = cur_epoch() & 1;
    const CtaId id2 = cta_id(); const int m = id2.m, j = id2.j;
    const uint32_t pk = park - S_X;
    auto tagged = [&](float lo, float hi) { return (pack_bf16(lo, hi) & ~1u) | tag; };
    auto store_vec = [&](const float* acc, int t, int i) {
      if (t >= 5) {
        st_relaxed_v4((uint4*)((char*)g_part + (size_t)((m * 8 + ((j + t) & 7)) * 3 + t - 5) * 16384 + i * 2048 + pk),
                      tagged(acc[i * 8], acc[i * 8 + 1]), tagged(acc[i * 8 + 2], acc[i * 8 + 3]), tagged(acc[i * 8 + 4], acc[i * 8 + 5]), tagged(acc[i * 8 + 6], acc[i * 8 + 7]));
      } else {
        const uint32_t w0 = pack_bf16(acc[i * 8], acc[i * 8 + 1]), w1 = pack_bf16(acc[i * 8 + 2], acc[i * 8 + 3]), w2 = pack_bf16(acc[i * 8 + 4], acc[i * 8 + 5]), w3 = pack_bf16(acc[i * 8 + 6], acc[i * 8 + 7]);
        if (t == 0) {
          if (i == 0) mbar_wait(B_GO, 0);
          const uint32_t pq = opaque(pk);
          char* dst = (char*)g_acc + (size_t)(m * 9 + 8) * 16384 + i * 4096 + (((pq >> 1) & 1023) | ((pq >> 3) & 1024));
          asm volatile("red.relaxed.gpu.global.add.noftz.v2.bf16x2 [%0], {%1,%2};" :: "l"(dst), "r"(w0), "r"(w1) : "memory");
          asm volatile("red.relaxed.gpu.global.add.noftz.v2.bf16x2 [%0], {%1,%2};" :: "l"(dst + 2048), "r"(w2), "r"(w3) : "memory");
        } else {
          asm volatile("red.relaxed.gpu.global.add.noftz.v4.bf16x2 [%0], {%1,%2,%3,%4};" :: "l"((char*)g_acc + (size_t)(m * 9 + ((j + t) & 7)) * 16384 + i * 2048 + pk), "r"(w0), "r"(w1), "r"(w2), "r"(w3) : "memory");
          if (i == 3 && t != 2) { __syncwarp(); arrive_one(B_PUB + 8 * (t >> 1)); }
        }
      }
    };
    auto own_part = [&](int s) { return (const char*)g_part + (size_t)((m * 8 + j) * 3 + s - 5) * 16384 + pk; };
    auto fetch = [&](int s) {
      const char* src = own_part(s);
      #pragma unroll
      for (int i = 0; i < 4; i++) cp_async16(park + (s & 1) * 16384 + i * 2048, src + i * 2048);
      cp_commit();
    };
    uint32_t missing = 0;
    #pragma unroll 1
    for (int u = 1; u < 9; u += 2) {
      run_pass<0, 5, 6>(accG, a, r, nop, nop);
      run_pass<1>(accU, a, r, nop, [&](int kb) {
        if (kb >= 1 && kb <= 4) store_vec(accG, u - 1, kb - 1);
        if (kb == 5 && u == 7) fetch(5); });
      run_pass<0, 0, 5>(accG, a, r, nop, [&](int kb) {
        if (u < 7) {
          if (kb >= 1) store_vec(accU, u, kb - 1);
        } else {
          if (kb == 1) {
            #pragma unroll
            for (int i = 0; i < 4; i++) store_vec(accU, 7, i);
            fetch(6);
          } else if (kb >= 3) {
            if (kb == 3) { mbar_wait(B_BASE, 0); mbar_wait(B_R, 0); cp_wait<0>(); }
            #pragma unroll
            for (int i = 2 * kb - 6; i < 2 * kb - 4; i++) {
              uint32_t v[4], w[4], f[4], b[4];
              lds128(park + 16384 + i * 2048, v[0], v[1], v[2], v[3]); lds128(park + i * 2048, w[0], w[1], w[2], w[3]);
              lds128(park + 6 * 16384 + i * 2048, f[0], f[1], f[2], f[3]); lds128(park + 7 * 16384 + i * 2048, b[0], b[1], b[2], b[3]);
              if (tag_bad(v[0], v[1], v[2], v[3], tag)) { missing |= 1u << i; v[0] = v[1] = v[2] = v[3] = 0; }
              if (tag_bad(w[0], w[1], w[2], w[3], tag)) { missing |= 16u << i; w[0] = w[1] = w[2] = w[3] = 0; }
              #pragma unroll
              for (int e = 0; e < 4; e++) { const uint32_t t = add_bf16x2(f[e], add_bf16x2(v[e], w[e])); accU[i * 8 + 2 * e] = bf_lo(t) + bf_lo(b[e]); accU[i * 8 + 2 * e + 1] = bf_hi(t) + bf_hi(b[e]); }
            }
          }
        } });
      r.ts = -1;
      if (u == 5) TSTAMP(5);
    }
    {
      const uint4* src = (const uint4*)own_part(7);
      uint32_t v[16];
      run_pass<0, 5, 6, false, true>(accG, a, r, nop, [&](int) {
        #pragma unroll
        for (int i = 0; i < 4; i++) ld_relaxed_v4(src + i * 128, v[i * 4], v[i * 4 + 1], v[i * 4 + 2], v[i * 4 + 3]);
      });
      #pragma unroll
      for (int i = 0; i < 4; i++) {
        const bool bad = tag_bad(v[i * 4], v[i * 4 + 1], v[i * 4 + 2], v[i * 4 + 3], tag);
        missing |= bad ? 256u << i : 0u;
        add_vec(accU + i * 8, bad ? 0u : v[i * 4], bad ? 0u : v[i * 4 + 1], bad ? 0u : v[i * 4 + 2], bad ? 0u : v[i * 4 + 3]);
      }
      if (missing) {
        #pragma unroll
        for (int i = 0; i < 4; i++) {
          #pragma unroll 1
          for (int s = 0; s < 3; s++)
            if (missing >> (4 * s + i) & 1) { uint32_t v0, v1, v2, v3; poll_v4((const uint4*)own_part(5 + s) + i * 128, v0, v1, v2, v3, tag); add_vec(accU + i * 8, v0, v1, v2, v3); }
        }
      }
      __syncwarp();
      wg_wait<0>();
      TSTAMP(6);
      #pragma unroll
      for (int i = 0; i < 32; i++) accU[i] += accG[i];
      const uint32_t pq = opaque(pk); const int lane = (pq >> 4) & 31, warp = (pq >> 9) & 3, wg = pq >> 13;
      const uint32_t stg = S_X + 4 * 16384 + wg * 8192 + warp * 2048;
      #pragma unroll
      for (int i = 0; i < 4; i++) {
        const int row = (lane & 7) + ((lane >> 3) & 1) * 8, chunk = 2 * i + (lane >> 4);
        asm volatile("stmatrix.sync.aligned.m8n8.x4.shared.b16 [%0], {%1,%2,%3,%4};" :: "r"(stg + row * 128 + ((chunk ^ (row & 7)) << 4)),
                     "r"(pack_bf16(accU[i * 8], accU[i * 8 + 1])), "r"(pack_bf16(accU[i * 8 + 2], accU[i * 8 + 3])), "r"(pack_bf16(accU[i * 8 + 4], accU[i * 8 + 5])), "r"(pack_bf16(accU[i * 8 + 6], accU[i * 8 + 7])) : "memory");
      }
      __syncwarp();
      TSTAMP(8);
      #pragma unroll
      for (int i = 0; i < 4; i++) {
        const int row = i * 4 + (lane >> 3), chunk = lane & 7;
        uint32_t o0, o1, o2, o3; lds128(stg + row * 128 + ((chunk ^ (row & 7)) << 4), o0, o1, o2, o3);
        *(uint4*)(out + (m * 128 + wg * 64 + warp * 16 + row) * D_ + j * 64 + chunk * 8) = make_uint4(o0, o1, o2, o3);
      }
    }
    }
    TSTAMP(7);
  }
}

typedef CUresult (*EncFn)(CUtensorMap*, CUtensorMapDataType, cuuint32_t, void*, const cuuint64_t*, const cuuint64_t*, const cuuint32_t*, const cuuint32_t*, CUtensorMapInterleave, CUtensorMapSwizzle, CUtensorMapL2promotion, CUtensorMapFloatOOBfill);
static void enc(EncFn f, CUtensorMap* tm, const void* base, int rank, uint64_t d0, uint64_t d1, uint64_t d2, uint64_t s1, uint64_t s2, uint32_t b0, uint32_t b1, uint32_t b2, CUtensorMapSwizzle sw) {
  cuuint64_t dims[3] = {d0, d1, d2}; cuuint64_t strides[2] = {s1, s2}; cuuint32_t box[3] = {b0, b1, b2}; cuuint32_t es[3] = {1, 1, 1};
  CUresult r = f(tm, CU_TENSOR_MAP_DATA_TYPE_BFLOAT16, rank, (void*)base, dims, strides, box, es, CU_TENSOR_MAP_INTERLEAVE_NONE, sw, CU_TENSOR_MAP_L2_PROMOTION_L2_128B, CU_TENSOR_MAP_FLOAT_OOB_FILL_NONE);
  if (r != CUDA_SUCCESS) fprintf(stderr, "tensor map encode failed %d\n", (int)r);
}

extern "C" void kernel_launch(void* const* d_in, const int* in_sizes, int n_in, void* d_out, int out_size) {
  static bool init = false;
  static Maps tm;
  if (!init) {
    void* fn = nullptr; cudaDriverEntryPointQueryResult st;
    cudaGetDriverEntryPoint("cuTensorMapEncodeTiled", &fn, cudaEnableDefault, &st);
    EncFn f = (EncFn)fn;
    void *xt, *yt; cudaGetSymbolAddress(&xt, g_xt); cudaGetSymbolAddress(&yt, g_yt);
    const CUtensorMapSwizzle S128 = CU_TENSOR_MAP_SWIZZLE_128B;
    enc(f, &tm.xraw3, d_in[0], 3, 64, L_, 9, D_ * 2, 128, 64, 16, 9, S128);
    enc(f, &tm.x2, d_in[0], 2, D_, L_, 1, D_ * 2, 0, 64, 128, 1, S128);
    enc(f, &tm.xt64, xt, 3, 64, D_ / 4, 128, 128, 32 * D_, 64, 16, 8, S128);
    enc(f, &tm.xt8, xt, 3, 64, D_ / 4, 128, 128, 32 * D_, 64, 2, 8, S128);
    enc(f, &tm.xt, xt, 2, 16 * D_, 128, 1, 32 * D_, 0, 64, 128, 1, S128);
    enc(f, &tm.yt, yt, 2, L_, D_, 1, L_ * 2, 0, 64, 64, 1, S128);
    enc(f, &tm.w1, d_in[10], 2, F_, D_, 1, F_ * 2, 0, 64, 96, 1, S128);
    enc(f, &tm.w3, d_in[11], 2, F_, D_, 1, F_ * 2, 0, 64, 96, 1, S128);
    enc(f, &tm.w2, d_in[12], 2, D_, F_, 1, D_ * 2, 0, 64, 96, 1, S128);
    enc(f, &tm.x8, d_in[0], 2, D_, L_, 1, D_ * 2, 0, 8, 128, 1, CU_TENSOR_MAP_SWIZZLE_NONE);
    enc(f, &tm.yt8, yt, 2, L_, D_, 1, L_ * 2, 0, 64, 8, 1, S128);
    cudaFuncSetAttribute(k_main, cudaFuncAttributeMaxDynamicSharedMemorySize, SMEM_BYTES);
    init = true;
  }
  SsmParams sp{(const __nv_bfloat16*)d_in[1], (const __nv_bfloat16*)d_in[2], (const __nv_bfloat16*)d_in[3], (const __nv_bfloat16*)d_in[4],
               (const __nv_bfloat16*)d_in[5], (const __nv_bfloat16*)d_in[6], (const __nv_bfloat16*)d_in[7]};
  k_main<<<NCTA, NTHR, SMEM_BYTES>>>(tm, sp, (const __nv_bfloat16*)d_in[8], (__nv_bfloat16*)d_out);
}
```

```cpp
#include <cuda_runtime.h>
#include <cuda.h>
#include <cuda_bf16.h>
#include <stdint.h>
#include <stdio.h>

__device__ __forceinline__ void wgmma_rs_n64_t1(float* d, uint32_t a0, uint32_t a1, uint32_t a2, uint32_t a3, uint64_t descB, int scaleD) {
  asm volatile("{\n.reg .pred p;\nsetp.ne.b32 p, %37, 0;\n"
    "wgmma.mma_async.sync.aligned.m64n64k16.f32.bf16.bf16 {%0,%1,%2,%3,%4,%5,%6,%7,%8,%9,%10,%11,%12,%13,%14,%15,%16,%17,%18,%19,%20,%21,%22,%23,%24,%25,%26,%27,%28,%29,%30,%31}, {%32,%33,%34,%35}, %36, p, 1, 1, 1;\n}\n"
    : "+f"(d[0]), "+f"(d[1]), "+f"(d[2]), "+f"(d[3]), "+f"(d[4]), "+f"(d[5]), "+f"(d[6]), "+f"(d[7]), "+f"(d[8]), "+f"(d[9]), "+f"(d[10]), "+f"(d[11]), "+f"(d[12]), "+f"(d[13]), "+f"(d[14]), "+f"(d[15]), "+f"(d[16]), "+f"(d[17]), "+f"(d[18]), "+f"(d[19]), "+f"(d[20]), "+f"(d[21]), "+f"(d[22]), "+f"(d[23]), "+f"(d[24]), "+f"(d[25]), "+f"(d[26]), "+f"(d[27]), "+f"(d[28]), "+f"(d[29]), "+f"(d[30]), "+f"(d[31])
    : "r"(a0), "r"(a1), "r"(a2), "r"(a3), "l"(descB), "r"(scaleD));
}
__device__ __forceinline__ void wgmma_ss_n48_t0(float* d, uint64_t descA, uint64_t descB, int scaleD) {
  asm volatile("{\n.reg .pred p;\nsetp.ne.b32 p, %26, 0;\n"
    "wgmma.mma_async.sync.aligned.m64n48k16.f32.bf16.bf16 {%0,%1,%2,%3,%4,%5,%6,%7,%8,%9,%10,%11,%12,%13,%14,%15,%16,%17,%18,%19,%20,%21,%22,%23}, %24, %25, p, 1, 1, 0, 0;\n}\n"
    : "+f"(d[0]), "+f"(d[1]), "+f"(d[2]), "+f"(d[3]), "+f"(d[4]), "+f"(d[5]), "+f"(d[6]), "+f"(d[7]), "+f"(d[8]), "+f"(d[9]), "+f"(d[10]), "+f"(d[11]), "+f"(d[12]), "+f"(d[13]), "+f"(d[14]), "+f"(d[15]), "+f"(d[16]), "+f"(d[17]), "+f"(d[18]), "+f"(d[19]), "+f"(d[20]), "+f"(d[21]), "+f"(d[22]), "+f"(d[23])
    : "l"(descA), "l"(descB), "r"(scaleD));
}
__device__ __forceinline__ void wgmma_rs_n32_t0(float* d, uint32_t a0, uint32_t a1, uint32_t a2, uint32_t a3, uint64_t descB, int scaleD) {
  asm volatile("{\n.reg .pred p;\nsetp.ne.b32 p, %21, 0;\n"
    "wgmma.mma_async.sync.aligned.m64n32k16.f32.bf16.bf16 {%0,%1,%2,%3,%4,%5,%6,%7,%8,%9,%10,%11,%12,%13,%14,%15}, {%16,%17,%18,%19}, %20, p, 1, 1, 0;\n}\n"
    : "+f"(d[0]), "+f"(d[1]), "+f"(d[2]), "+f"(d[3]), "+f"(d[4]), "+f"(d[5]), "+f"(d[6]), "+f"(d[7]), "+f"(d[8]), "+f"(d[9]), "+f"(d[10]), "+f"(d[11]), "+f"(d[12]), "+f"(d[13]), "+f"(d[14]), "+f"(d[15])
    : "r"(a0), "r"(a1), "r"(a2), "r"(a3), "l"(descB), "r"(scaleD));
}

#define PFLA 6
#define SLPOS 2
#define INCFIRST
#define TANHSILU
constexpr int L_ = 2048, D_ = 576, F_ = 4608;
constexpr int NFFN = 128, NCTA = 132, NTHR = 384;
constexpr int STG_BYTES = 12288;
constexpr uint32_t S_X = 1024;
constexpr uint32_t S_RING = S_X + 147456;
constexpr uint32_t S_MISC = S_RING + 6 * STG_BYTES;
constexpr uint32_t S_BAR = S_MISC + 8320, S_DSK = S_BAR + 512, S_DUMMY = S_DSK + 256;
constexpr int SMEM_BYTES = S_DUMMY + 256 + 768 - 1024;
constexpr uint32_t B_FULL = S_BAR, B_EMPTY = S_BAR + 64, B_X = S_BAR + 128  , B_PFREE = S_BAR + 176, B_BASE = S_BAR + 184  ,
                   B_RAW = S_BAR + 200, B_LN = S_BAR + 208, B_U = S_BAR + 216  , B_KDONE = S_BAR + 232  , B_CDONE = S_BAR + 248  ,
                   B_RDONE = S_BAR + 264  , B_H = S_BAR + 280, B_YDONE = S_BAR + 288, B_PP = S_BAR + 296  , B_GO = S_BAR + 312, B_PUB = S_BAR + 320  , B_R = S_BAR + 344, B_H8 = S_BAR + 352, B_EP = S_BAR + 360, B_LN2 = S_BAR + 368;
constexpr uint32_t S_LN = S_RING + 3 * STG_BYTES;
constexpr uint32_t S_U = S_LN + 20480;
__device__ __forceinline__ uint32_t s_w_of(int ch) { return ch < 2 ? S_LN + ch * 8256 : (ch == 2 ? S_X + 8 * 16384 : S_MISC); }
__host__ __device__ constexpr int xslot(int kb) { return kb < 3 ? kb : (kb < 6 ? kb + 1 : (kb == 6 ? 3 : kb)); }

__device__ __nv_bfloat16 g_xt[D_ * L_];
__device__ __nv_bfloat16 g_yt[D_ * L_];
__device__ uint4 g_part[16 * 8 * 3 * 1024];
__device__ uint4 g_acc[16 * 9 * 1024];
__device__ unsigned int g_cnt_acc[16 * 9 * 8];
__device__ unsigned int g_ticket, g_cnt_all, g_cnt_y, g_cnt_ys;
#define TSTAMP(i)
#define GSTAMP(i)
#define TSTAMP1(w, i)

#define CT(i)
#define KT(i)
__device__ __forceinline__ uint32_t smem_u32(const void* p) { return (uint32_t)__cvta_generic_to_shared(p); }
__device__ __forceinline__ void mbar_init(uint32_t bar, uint32_t cnt) { asm volatile("mbarrier.init.shared::cta.b64 [%0], %1;" :: "r"(bar), "r"(cnt)); }
__device__ __forceinline__ void mbar_expect_tx(uint32_t bar, uint32_t bytes) { asm volatile("mbarrier.arrive.expect_tx.shared::cta.b64 _, [%0], %1;" :: "r"(bar), "r"(bytes) : "memory"); }
__device__ __forceinline__ void mbar_arrive(uint32_t bar) { asm volatile("mbarrier.arrive.shared::cta.b64 _, [%0];" :: "r"(bar) : "memory"); }
__device__ __forceinline__ bool mbar_try_wait(uint32_t bar, uint32_t parity) {
  uint32_t ok;
  asm volatile("{\n.reg .pred p;\nmbarrier.try_wait.parity.shared::cta.b64 p, [%1], %2;\nselp.u32 %0, 1, 0, p;\n}\n" : "=r"(ok) : "r"(bar), "r"(parity) : "memory");
  return ok;
}
__device__ __forceinline__ void mbar_wait(uint32_t bar, uint32_t parity) {
  asm volatile("{\n.reg .pred p;\n.reg .u32 c;\nmov.u32 c, 0;\n"
               "WAIT_LOOP:\nmbarrier.try_wait.parity.shared::cta.b64 p, [%0], %1;\nadd.u32 c, c, 1;\n@!p setp.gt.u32 p, c, 1024;\n@!p bra WAIT_LOOP;\n}\n" :: "r"(bar), "r"(parity) : "memory");
}
__device__ __forceinline__ void mbar_spin(uint32_t bar, uint32_t parity) {
  asm volatile("{\n.reg .pred p;\n.reg .u32 c;\nmov.u32 c, 0;\n"
               "SPIN_LOOP:\nmbarrier.test_wait.parity.shared::cta.b64 p, [%0], %1;\nadd.u32 c, c, 1;\n@!p setp.gt.u32 p, c, 0x100000;\n@!p bra SPIN_LOOP;\n}\n" :: "r"(bar), "r"(parity) : "memory");
}
__device__ __forceinline__ void flag_wait(const unsigned int* f, unsigned int val, unsigned int ns) {
  unsigned int v;
  #pragma unroll 1
  for (int it = 0; it < 16384; it++) {
    asm volatile("ld.relaxed.gpu.global.u32 %0, [%1];" : "=r"(v) : "l"(f) : "memory");
    if (v == val) break;
    __nanosleep(ns);
  }
  asm volatile("ld.acquire.gpu.global.u32 %0, [%1];" : "=r"(v) : "l"(f) : "memory");
}
__device__ __forceinline__ void red_add(unsigned int* p) { asm volatile("red.relaxed.gpu.global.add.u32 [%0], 1;" :: "l"(p) : "memory"); }
__device__ __forceinline__ void fence_gpu() { asm volatile("fence.acq_rel.gpu;" ::: "memory"); }
__device__ __forceinline__ void fence_async() { asm volatile("fence.proxy.async.global;" ::: "memory"); }
__device__ __forceinline__ void fence_async_smem() { asm volatile("fence.proxy.async.shared::cta;" ::: "memory"); }
__device__ __forceinline__ unsigned int cur_epoch() { mbar_wait(B_EP, 0); unsigned int v; asm volatile("ld.shared.b32 %0, [%1];" : "=r"(v) : "r"(S_DSK + 196) : "memory"); return v; }
__device__ __forceinline__ void tma2d(uint32_t dst, const CUtensorMap* tm, int c0, int c1, uint32_t bar) {
  asm volatile("cp.async.bulk.tensor.2d.shared::cluster.global.mbarrier::complete_tx::bytes [%0], [%1, {%3, %4}], [%2];" :: "r"(dst), "l"(tm), "r"(bar), "r"(c0), "r"(c1) : "memory");
}
__device__ __forceinline__ void tma3d(uint32_t dst, const CUtensorMap* tm, int c0, int c1, int c2, uint32_t bar) {
  asm volatile("cp.async.bulk.tensor.3d.shared::cluster.global.mbarrier::complete_tx::bytes [%0], [%1, {%3, %4, %5}], [%2];" :: "r"(dst), "l"(tm), "r"(bar), "r"(c0), "r"(c1), "r"(c2) : "memory");
}
__device__ __forceinline__ void bulk_g2s(uint32_t dst, const void* src, uint32_t bytes, uint32_t bar) {
  asm volatile("cp.async.bulk.shared::cluster.global.mbarrier::complete_tx::bytes [%0], [%1], %2, [%3];" :: "r"(dst), "l"(src), "r"(bytes), "r"(bar) : "memory");
}
__device__ __forceinline__ void prefetch_tmap(const CUtensorMap* tm) { asm volatile("prefetch.tensormap [%0];" :: "l"(tm) : "memory"); }
__device__ __forceinline__ void wg_fence() { asm volatile("wgmma.fence.sync.aligned;" ::: "memory"); }
__device__ __forceinline__ void wg_commit() { asm volatile("wgmma.commit_group.sync.aligned;" ::: "memory"); }
template <int N> __device__ __forceinline__ void wg_wait() { asm volatile("wgmma.wait_group.sync.aligned %0;" :: "n"(N) : "memory"); }
__device__ __forceinline__ void bar_sync(int id, int n) { asm volatile("bar.sync %0, %1;" :: "r"(id), "r"(n) : "memory"); }
__device__ __forceinline__ void bar_arrive(int id, int n) { asm volatile("bar.arrive %0, %1;" :: "r"(id), "r"(n) : "memory"); }
__device__ __forceinline__ uint32_t pack_bf16(float lo, float hi) { uint32_t r; asm("cvt.rn.bf16x2.f32 %0, %1, %2;" : "=r"(r) : "f"(hi), "f"(lo)); return r; }
__device__ __forceinline__ float bf_lo(uint32_t v) { return __uint_as_float(v << 16); }
__device__ __forceinline__ float bf_hi(uint32_t v) { return __uint_as_float(v & 0xFFFF0000u); }
__device__ __forceinline__ float bf_round(float v) { return bf_lo(pack_bf16(v, v)); }
__device__ __forceinline__ uint32_t mul_bf16x2(uint32_t a, uint32_t b) { uint32_t r; asm("mul.rn.bf16x2 %0, %1, %2;" : "=r"(r) : "r"(a), "r"(b)); return r; }
__device__ __forceinline__ uint32_t add_bf16x2(uint32_t a, uint32_t b) { uint32_t r; asm("add.rn.bf16x2 %0, %1, %2;" : "=r"(r) : "r"(a), "r"(b)); return r; }
__device__ __forceinline__ uint32_t sub_bf16x2(uint32_t a, uint32_t b) { uint32_t r; asm("sub.rn.bf16x2 %0, %1, %2;" : "=r"(r) : "r"(a), "r"(b)); return r; }
__device__ __forceinline__ void ldsm_x4(uint32_t addr, uint32_t& r0, uint32_t& r1, uint32_t& r2, uint32_t& r3) {
  asm volatile("ldmatrix.sync.aligned.m8n8.x4.shared.b16 {%0,%1,%2,%3}, [%4];" : "=r"(r0), "=r"(r1), "=r"(r2), "=r"(r3) : "r"(addr) : "memory");
}
__device__ __forceinline__ void ldsm_x4t(uint32_t addr, uint32_t& r0, uint32_t& r1, uint32_t& r2, uint32_t& r3) {
  asm volatile("ldmatrix.sync.aligned.m8n8.x4.trans.shared.b16 {%0,%1,%2,%3}, [%4];" : "=r"(r0), "=r"(r1), "=r"(r2), "=r"(r3) : "r"(addr) : "memory");
}
__device__ __forceinline__ float silu_f(float g) {
  const float hh = 0.5f * g; float th; asm("tanh.approx.f32 %0, %1;" : "=f"(th) : "f"(hh)); return fmaf(hh, th, hh);
  float e; asm("ex2.approx.ftz.f32 %0, %1;" : "=f"(e) : "f"(g * -1.4426950408889634f));
  float r; asm("rcp.approx.ftz.f32 %0, %1;" : "=f"(r) : "f"(1.0f + e));
  return g * r;
}
__device__ __forceinline__ void sts128(uint32_t addr, uint32_t a, uint32_t b, uint32_t c, uint32_t d) { asm volatile("st.shared.v4.b32 [%0], {%1,%2,%3,%4};" :: "r"(addr), "r"(a), "r"(b), "r"(c), "r"(d) : "memory"); }
__device__ __forceinline__ void sts64(uint32_t addr, uint32_t a, uint32_t b) { asm volatile("st.shared.v2.b32 [%0], {%1,%2};" :: "r"(addr), "r"(a), "r"(b) : "memory"); }
__device__ __forceinline__ void sts32(uint32_t addr, uint32_t a) { asm volatile("st.shared.b32 [%0], %1;" :: "r"(addr), "r"(a) : "memory"); }
__device__ __forceinline__ void lds128(uint32_t addr, uint32_t& a, uint32_t& b, uint32_t& c, uint32_t& d) { asm volatile("ld.shared.v4.b32 {%0,%1,%2,%3}, [%4];" : "=r"(a), "=r"(b), "=r"(c), "=r"(d) : "r"(addr) : "memory"); }
__device__ __forceinline__ void lds64(uint32_t addr, uint32_t& a, uint32_t& b) { asm volatile("ld.shared.v2.b32 {%0,%1}, [%2];" : "=r"(a), "=r"(b) : "r"(addr) : "memory"); }
__device__ __forceinline__ uint32_t lds32(uint32_t addr) { uint32_t a; asm volatile("ld.shared.b32 %0, [%1];" : "=r"(a) : "r"(addr) : "memory"); return a; }
__device__ __forceinline__ float ldsf(uint32_t addr) { float a; asm volatile("ld.shared.f32 %0, [%1];" : "=f"(a) : "r"(addr) : "memory"); return a; }
__device__ __forceinline__ uint32_t opaque(uint32_t v) { uint32_t r; asm volatile("mov.b32 %0, %1;" : "=r"(r) : "r"(v)); return r; }
__device__ __forceinline__ void cp_async16(uint32_t dst, const void* src) { asm volatile("cp.async.cg.shared.global [%0], [%1], 16;" :: "r"(dst), "l"(src) : "memory"); }
__device__ __forceinline__ void cp_commit() { asm volatile("cp.async.commit_group;" ::: "memory"); }
template <int N> __device__ __forceinline__ void cp_wait() { asm volatile("cp.async.wait_group %0;" :: "n"(N) : "memory"); }
__device__ __forceinline__ void st_relaxed_v4(uint4* p, uint32_t a, uint32_t b, uint32_t c, uint32_t d) {
  asm volatile("st.relaxed.gpu.global.v4.b32 [%0], {%1,%2,%3,%4};" :: "l"(p), "r"(a), "r"(b), "r"(c), "r"(d) : "memory");
}
__device__ __forceinline__ void ld_relaxed_v4(const uint4* p, uint32_t& a, uint32_t& b, uint32_t& c, uint32_t& d) {
  asm volatile("ld.relaxed.gpu.global.v4.b32 {%0,%1,%2,%3}, [%4];" : "=r"(a), "=r"(b), "=r"(c), "=r"(d) : "l"(p) : "memory");
}
__device__ __forceinline__ bool tag_bad(uint32_t a, uint32_t b, uint32_t c, uint32_t d, uint32_t tag) { return (((a ^ tag) | (b ^ tag) | (c ^ tag) | (d ^ tag)) & 1u) != 0; }
__device__ __forceinline__ void poll_v4(const uint4* p, uint32_t& a, uint32_t& b, uint32_t& c, uint32_t& d, uint32_t tag) {
  int it = 0;
  do { ld_relaxed_v4(p, a, b, c, d); } while (tag_bad(a, b, c, d, tag) && ++it < 4096);
}
__device__ __forceinline__ void add_vec(float* f, uint32_t v0, uint32_t v1, uint32_t v2, uint32_t v3) {
  f[0] += bf_lo(v0); f[1] += bf_hi(v0); f[2] += bf_lo(v1); f[3] += bf_hi(v1); f[4] += bf_lo(v2); f[5] += bf_hi(v2); f[6] += bf_lo(v3); f[7] += bf_hi(v3);
}

struct cplx { float re, im; };
__device__ __forceinline__ cplx cmul(cplx a, cplx b) { return {fmaf(a.re, b.re, -a.im * b.im), fmaf(a.re, b.im, a.im * b.re)}; }
__device__ __forceinline__ cplx cexp_f(float ar, float ai) {
  float mag; asm("ex2.approx.f32 %0, %1;" : "=f"(mag) : "f"(ar * 1.4426950408889634f));
  const float k = rintf(ai * 0.15915494309189535f);
  float r = fmaf(ai, 0.15915494309189535f, -k);
  r = fmaf(ai, 6.4206383e-9f, r);
  r *= 6.283185307179586f;
  float sn, cs; asm("sin.approx.f32 %0, %1;" : "=f"(sn) : "f"(r)); asm("cos.approx.f32 %0, %1;" : "=f"(cs) : "f"(r));
  return {mag * cs, mag * sn};
}
__device__ __forceinline__ float bf2f(__nv_bfloat16 v) { return __bfloat162float(v); }

constexpr int KG_B = 32768, KG_TAB = 2688;

struct SsmParams { const __nv_bfloat16 *are, *aim, *bre, *bim, *cre, *cim, *logdt; };
struct ModeRaw { uint32_t are, aim, bre, bim, cre, cim; __nv_bfloat16 ldt; };
__device__ __forceinline__ ModeRaw load_mode(const SsmParams& p, int d, int t128) {
  const int o = d * 64 + t128;
  auto ld = [&](const __nv_bfloat16* b) { return __ldg((const uint32_t*)b + o); };
  return {ld(p.are), ld(p.aim), ld(p.bre), ld(p.bim), ld(p.cre), ld(p.cim), __ldg(p.logdt + d + (t128 >> 6))};
}

__device__ __forceinline__ void layer_norm16(int tid_);
__device__ __forceinline__ void kgen_powers(const ModeRaw& mr, int wg, int t128_, int row0, bool g_first) {
  const int t128 = opaque(t128_);
  const uint32_t scr = S_X + wg * 65536;
  const int warp = t128 >> 5, lane = t128 & 31;
  cplx cb[2], z1[2], zq[2];
  const float dt = bf_round(expf(bf2f(mr.ldt)));
  #pragma unroll
  for (int c = 0; c < 2; c++) {
    auto f = [&](uint32_t v) { return c ? bf_hi(v) : bf_lo(v); };
    const float ar = dt * f(mr.are), ai = dt * f(mr.aim);
    cb[c] = cmul({f(mr.cre), f(mr.cim)}, {dt * f(mr.bre), dt * f(mr.bim)});
    z1[c] = cexp_f(ar, ai); zq[c] = cexp_f(ar * 256.f, ai * 256.f);
  }
  KT(12);
  uint32_t ad[8];
  #pragma unroll
  for (int i = 0; i < 8; i++) ad[i] = scr + KG_B + ((warp & 1) * 2 + (lane >> 4)) * 6144 + (warp >> 1) * 3072 + (lane & 1) * 8 + ((((lane >> 1) & 7) ^ i) << 4);
  cplx z2[2];
  {
    auto put = [&](int b, const cplx* v) { sts64(ad[b & 7] + b * 128, pack_bf16(v[0].re, -v[0].im), pack_bf16(v[1].re, -v[1].im)); };
    cplx e[2], o[2], h[2], h0[2], h4[2];
    #pragma unroll
    for (int c = 0; c < 2; c++) { z2[c] = cmul(z1[c], z1[c]); e[c] = cb[c]; o[c] = cmul(cb[c], z1[c]); }
    #pragma unroll
    for (int i = 0; i < 4; i++) {
      put(2 * i, e); put(2 * i + 1, o);
      #pragma unroll
      for (int c = 0; c < 2; c++) {
        h[c] = cmul(e[c], zq[c]);
        if (i == 0) h0[c] = h[c];
        if (i == 2) h4[c] = h[c];
        if (i < 3) { e[c] = cmul(e[c], z2[c]); o[c] = cmul(o[c], z2[c]); }
      }
      put(8 + i, h);
    }
    #pragma unroll
    for (int i = 0; i < 7; i++) {
      #pragma unroll
      for (int c = 0; c < 2; c++) { h0[c] = cmul(h0[c], zq[c]); if (i < 2) h4[c] = cmul(h4[c], zq[c]); }
      put(i < 2 ? 12 + 2 * i : 14 + i, h0);
      if (i < 2) put(13 + 2 * i, h4);
    }
  }
  KT(13);
  if (row0 >= 0) layer_norm16(wg * 128 + t128);
  {
    #pragma unroll
    for (int i = 0; i < 8; i++) ad[i] += ((warp & 1) * 2 + (lane >> 4)) * 2048 + (warp >> 1) * 1024 - KG_B;
    cplx y[2][2], z16[2];
    #pragma unroll
    for (int c = 0; c < 2; c++) { const cplx z4 = cmul(z2[c], z2[c]); y[0][c] = {1.f, 0.f}; y[1][c] = cmul(z4, z4); z16[c] = cmul(y[1][c], y[1][c]); }
    #pragma unroll 1
    for (int jo = 0; jo < 4096; jo += 1024) {
      #pragma unroll
      for (int jj = 0; jj < 8; jj++) {
        sts64(ad[jj] + jo + jj * 128, pack_bf16(y[jj & 1][0].re, y[jj & 1][0].im), pack_bf16(y[jj & 1][1].re, y[jj & 1][1].im));
        #pragma unroll
        for (int c = 0; c < 2; c++) y[jj & 1][c] = cmul(y[jj & 1][c], z16[c]);
      }
    }
  }
  KT(14);
  fence_async_smem();
}
__device__ __forceinline__ void kgen_finish(int wg, int t128_, bool ln, bool g_first) {
  const int t128 = opaque(t128_);
  const uint32_t scr = S_X + wg * 65536;
  const int warp = t128 >> 5, lane = t128 & 31;
  bar_sync(2 + wg, 128);
  KT(15);
  float dd[24];
  {
    wg_fence();
    const uint64_t da = ((uint64_t)0x40000040u << 32) | opaque((scr >> 4) | 0x10000u), db = da + KG_B / 16;
    #pragma unroll
    for (int ks = 0; ks < 16; ks++) wgmma_ss_n48_t0(dd, da + (ks >> 2) * 512 + (ks & 3) * 2, db + (ks >> 2) * 384 + (ks & 3) * 2, ks != 0);
    wg_commit();
    wg_wait<0>();
  }
  KT(16);
  bar_sync(2 + wg, 128);
  {
    const int g = lane >> 2, q = lane & 3, hi = warp >> 1;
    const uint32_t tb = scr + hi * KG_TAB;
    #pragma unroll
    for (int rr = 0; rr < 2; rr++) {
      const int jj = (warp & 1) * 16 + g + rr * 8;
      float v[6];
      #pragma unroll
      for (int b = 0; b < 3; b++) { v[b * 2] = hi ? dd[12 + b * 4 + rr * 2] : dd[b * 4 + rr * 2]; v[b * 2 + 1] = hi ? dd[12 + b * 4 + rr * 2 + 1] : dd[b * 4 + rr * 2 + 1]; }
      sts64(tb + (8 * jj + 2 * q) * 4, __float_as_uint(v[0]), __float_as_uint(v[1]));
      sts64(tb + (q < 2 ? 256 + 4 * jj + 2 * q : 256 + 64 * q + 2 * jj) * 4, __float_as_uint(v[2]), __float_as_uint(v[3]));
      if (q < 2) { sts32(tb + (512 + 64 * q + jj) * 4, __float_as_uint(v[4])); sts32(tb + (544 + 64 * q + jj) * 4, __float_as_uint(v[5])); }
      else if (q == 2 && jj == 0) sts32(tb + 640 * 4, __float_as_uint(v[4]));
    }
  }
  KT(17);
  if (ln && wg == 0) mbar_wait(B_LN2, 0);
  bar_sync(2 + wg, 128);
  #pragma unroll
  for (int c = 0; c < 2; c++) {
    const uint32_t t0 = scr + c * KG_TAB, wp = s_w_of(wg * 2 + c) + 64 + t128 * 16;
    const int t = t128;
    float k0, k1, k2, k3, kp;
    if (warp < 2) {
      uint32_t a0, a1, a2, a3; lds128(t0 + 16 * t, a0, a1, a2, a3);
      k0 = __uint_as_float(a0); k1 = __uint_as_float(a1); k2 = __uint_as_float(a2); k3 = __uint_as_float(a3);
      kp = ldsf(t0 + 16 * t - (t ? 4 : 0)); if (t == 0) kp = 0.f;
    } else {
      uint32_t a0, a1; lds64(t0 + (128 + 2 * t) * 4, a0, a1);
      k0 = k1 = __uint_as_float(a0); k2 = __uint_as_float(a1); k3 = ldsf(t0 + (130 + 2 * t) * 4);
      kp = ldsf(t0 + (t == 64 ? 255 : 128 + 2 * t) * 4);
    }
    const float s0 = ldsf(t0 + (384 + t) * 4), s1 = ldsf(t0 + (385 + t) * 4);
    const int ph = t & 3, b3 = 512 + 2 * (t >> 2);
    const float a0 = ldsf(t0 + (b3 + (ph >> 1)) * 4), c0 = ldsf(t0 + (b3 + ((ph + 1) >> 1)) * 4);
    const float a1 = ldsf(t0 + (b3 + 64 + (ph >> 1)) * 4), c1 = ldsf(t0 + (b3 + 64 + ((ph + 1) >> 1)) * 4);
    sts128(wp, pack_bf16(k0, kp), pack_bf16(k1, k0), pack_bf16(k2, k1), pack_bf16(k3, k2));
    const float m = (t & 1) ? s1 : s0;
    sts128(wp + 2048, pack_bf16(s0, s0), pack_bf16(s0, s0), pack_bf16(m, s0), pack_bf16(s1, m));
    const float f0 = ph == 1 ? a0 : c0, f1 = ph == 1 ? a1 : c1;
    sts128(wp + 4096, pack_bf16(f0, a0), pack_bf16(c0, f0), pack_bf16(c0, c0), pack_bf16(c0, c0));
    sts128(wp + 6144, pack_bf16(f1, a1), pack_bf16(c1, f1), pack_bf16(c1, c1), pack_bf16(c1, c1));
    if (t < 4) sts128(wp - 64, 0, 0, 0, 0);
    if (!ln && t < 112) sts128(S_U - 3584 + c * 1792 + t * 16, 0, 0, 0, 0);
  }
}

template <int P> __device__ __forceinline__ void conv_step(float* acc, const uint32_t* fr, uint32_t db) {
  uint32_t lo; asm volatile("sub.u32 %0, %1, %2;" : "=r"(lo) : "r"(db), "n"(32 * P - 256 * 3));
  uint64_t d = ((uint64_t)0x40000040u << 32) | lo;
  #pragma unroll
  for (int sg = 3; sg >= P / 8; sg--) wgmma_rs_n32_t0(acc + 16 * sg, fr[0], fr[1], fr[2], fr[3], d - 256 * (3 - sg), P != 0);
}
template <int I, int I1> struct ConvPairs {
  static __device__ __forceinline__ void run(float* acc, const uint32_t* fr, uint32_t db) {
    conv_step<I>(acc, fr + I * 4, db); conv_step<31 - I>(acc, fr + (31 - I) * 4, db);
    ConvPairs<I + 1, I1>::run(acc, fr, db);
  }
};
template <int I1> struct ConvPairs<I1, I1> { static __device__ __forceinline__ void run(float*, const uint32_t*, uint32_t) {} };

__device__ __forceinline__ void conv_reduce(uint32_t s_r, int t128, __nv_bfloat16* yrow) {
  #pragma unroll
  for (int h = 0; h < 2; h++) {
    const int cc = t128 + h * 128;
    uint32_t v[4][4];
    #pragma unroll
    for (int b = 0; b < 4; b++) {
      lds128(s_r + b * 4096 + cc * 16, v[b][0], v[b][1], v[b][2], v[b][3]);
      if (h == 0 && b > (cc >> 1)) { v[b][0] = v[b][1] = v[b][2] = v[b][3] = 0; }
    }
    uint32_t o[4];
    #pragma unroll
    for (int e = 0; e < 4; e++) { const uint32_t p = add_bf16x2(v[0][e], v[1][e]), q = add_bf16x2(v[2][e], v[3][e]); o[e] = add_bf16x2(p, q); }
    *(uint4*)(yrow + cc * 8) = make_uint4(o[0], o[1], o[2], o[3]);
  }
}
__device__ __forceinline__ void conv_one(int wg, int c, int t128_, int uphase, __nv_bfloat16* y0) {
  const int t128 = opaque(t128_), ch = wg * 2 + c;
  const uint32_t s_w = s_w_of(ch), s_r = S_X + wg * 65536 + 49152;
  const int warp = t128 >> 5, lane = t128 & 31;
  float acc[64];
  uint32_t fr[128];
  const uint32_t wa = s_w + 64 + (warp * 16 + (lane >> 2) - 2 * (lane & 3)) * 4;
  const uint32_t zero = lds32(s_w);
  auto ld = [&](int p) { fr[p * 4] = lds32(wa + p * 256); fr[p * 4 + 1] = lds32(wa + p * 256 + 32); fr[p * 4 + 2] = lds32(wa + p * 256 - 32);
                         asm volatile("xor.b32 %0, %1, %2;" : "=r"(fr[p * 4 + 3]) : "r"(fr[p * 4]), "r"(zero)); };
  const uint32_t db = ((S_U >> 4) | 0x10000u) + ch * 2;
  #pragma unroll
  for (int p = 0; p < 32; p++) ld(p);
  CT(0);
  if (c == 0) mbar_wait(B_U, uphase);
  mbar_wait(B_PP + 8 * wg, wg ? c ^ 1 : c);
  CT(1);
  wg_fence();
  ConvPairs<0, 16>::run(acc, fr, db);
  wg_commit();
  if (lane == 0) mbar_arrive(B_PP + 8 - 8 * wg);
  if (c == 1) conv_reduce(s_r, t128, y0);
  CT(2);
  wg_wait<0>();
  CT(3);
  if (c == 1 && lane == 0) mbar_arrive(B_CDONE);
  if (c == 1) bar_sync(2 + wg, 128);
  const int col = 8 * (lane >> 4) + (lane & 7) + warp;
  const uint32_t ra = s_r + warp * 4096 + (col * 16 + ((lane >> 3) & 1) * 8) * 2;
  #pragma unroll
  for (int v = 0; v < 8; v++)
    asm volatile("stmatrix.sync.aligned.m8n8.x4.trans.shared.b16 [%0], {%1,%2,%3,%4};" :: "r"((v == 7 && col >= 16) ? S_DUMMY : ra + v * 512),
                 "r"(pack_bf16(acc[v * 8], acc[v * 8 + 1])), "r"(pack_bf16(acc[v * 8 + 2], acc[v * 8 + 3])), "r"(pack_bf16(acc[v * 8 + 4], acc[v * 8 + 5])), "r"(pack_bf16(acc[v * 8 + 6], acc[v * 8 + 7])) : "memory");
  bar_sync(2 + wg, 128);
  CT(4);
}

__device__ __forceinline__ void layer_norm16(int tid_) {
  const int tid = opaque(tid_), row = tid >> 4, l16 = tid & 15;
  const bool g_first = true; (void)g_first;
  const uint32_t ra = S_LN + (l16 >> 3) * 2048 + row * 128 + (((l16 & 7) ^ (row & 7)) << 4);
  uint32_t v[20];
  KT(20);
  mbar_wait(B_RAW, 0);
  KT(21);
  #pragma unroll
  for (int i = 0; i < 4; i++) lds128(ra + i * 4096, v[i * 4], v[i * 4 + 1], v[i * 4 + 2], v[i * 4 + 3]);
  v[16] = v[17] = v[18] = v[19] = 0;
  if (l16 < 8) lds128(ra + 16384, v[16], v[17], v[18], v[19]);
  float s0 = 0.f, s1 = 0.f, q0 = 0.f, q1 = 0.f;
  #pragma unroll
  for (int e = 0; e < 20; e++) { const float lo = bf_lo(v[e]), hi = bf_hi(v[e]); s0 += lo; s1 += hi; q0 = fmaf(lo, lo, q0); q1 = fmaf(hi, hi, q1); }
  float s = s0 + s1, ss = q0 + q1;
  #pragma unroll
  for (int o = 8; o; o >>= 1) { s += __shfl_xor_sync(0xffffffffu, s, o); ss += __shfl_xor_sync(0xffffffffu, ss, o); }
  const float mean = s * (1.f / D_), var = fmaxf(fmaf(-mean, mean, ss * (1.f / D_)), 0.f);
  const uint32_t mb = pack_bf16(mean, mean);
  const float rs = 1.0f / bf_round(sqrtf(bf_round(bf_round(var) + 1e-5f)));
  const uint32_t rh = pack_bf16(rs, rs), rl = pack_bf16(rs - bf_lo(rh), rs - bf_lo(rh));
  KT(22);
  #pragma unroll
  for (int e = 0; e < 20; e++) { const uint32_t dd = sub_bf16x2(v[e], mb); asm("fma.rn.bf16x2 %0, %1, %2, %3;" : "=r"(v[e]) : "r"(dd), "r"(rh), "r"(mul_bf16x2(dd, rl))); }
  #pragma unroll
  for (int i = 0; i < 5; i++) if (i < 4 || l16 < 8) sts128(ra + i * 4096, v[i * 4], v[i * 4 + 1], v[i * 4 + 2], v[i * 4 + 3]);
  KT(23);
  bar_sync(4, 256);
  {
    const int warp = tid >> 5, lane = tid & 31, r = lane & 7, e = lane >> 3, tok = (r >> 1) * 4 + (r & 1) + (e & 1) * 2;
    const uint32_t la = S_LN + (warp >> 2) * 2048 + tok * 128 + ((((warp & 3) * 2 + (e >> 1)) ^ (tok & 7)) << 4), ta = S_LN + 18432 + warp * 512 + lane * 8;
    #pragma unroll
    for (int i = 0; i < 5; i++) if (i < 4 || warp < 4) ldsm_x4t(la + i * 4096, v[i * 4], v[i * 4 + 1], v[i * 4 + 2], v[i * 4 + 3]);
    #pragma unroll
    for (int i = 0; i < 5; i++) if (i < 4 || warp < 4) { sts64(ta + i * 4096, v[i * 4], v[i * 4 + 1]); sts64(ta + i * 4096 + 256, v[i * 4 + 2], v[i * 4 + 3]); }
  }
  fence_async_smem();
  __syncwarp();
  if ((tid & 31) == 0) mbar_arrive(B_LN);
  KT(24);
}

__device__ __forceinline__ void ssm_phase(const SsmParams& p, ModeRaw mr, int wg, int d0, int npair, int row0, int t128) {
  int d = d0 + wg * 2;
  #pragma unroll 1
  for (int it = 0; it < npair; it++, d += 4) {
    kgen_powers(mr, wg, t128, row0, it == 0);
    kgen_finish(wg, t128, row0 >= 0, it == 0);
    fence_async_smem();
    __syncwarp();
    if ((t128 & 31) == 0) mbar_arrive(B_KDONE + 8 * wg);
    bar_sync(2 + wg, 128);
    if (it == 0) { TSTAMP(10); GSTAMP(5); }
    #pragma unroll 1
    for (int c = 0; c < 2; c++) conv_one(wg, c, t128, it & 1, g_yt + d * L_);
    conv_reduce(S_X + wg * 65536 + 49152, opaque(t128), g_yt + (d + 1) * L_);
    fence_async_smem();
    __syncwarp();
    if ((t128 & 31) == 0) mbar_arrive(B_RDONE + 8 * wg);
    if (it + 1 < npair) { mr = load_mode(p, d + 4, t128); bar_sync(4, 256); }
  }
  if ((t128 & 31) == 0) mbar_arrive(B_YDONE);
}

#define RELPOS 6
#define PACE 600
struct Ring { bool ready; int ts; unsigned int wt; };
__device__ __forceinline__ void arrive_one(uint32_t bar) {
  asm volatile("{\n.reg .pred p;\nelect.sync _|p, 0xffffffff;\n@p mbarrier.arrive.shared::cta.b64 _, [%0];\n}\n" :: "r"(bar) : "memory");
}

template <int PH, int KB0 = 0, int KB1 = 6, bool FIRST = false, bool LAST = false, class Pre, class Slice>
__device__ __forceinline__ void run_pass(float* acc, uint32_t* a, Ring& r, Pre pre, Slice slice) {
  #pragma unroll
  for (int kb = KB0; kb < KB1; kb++) {
    pre(kb);
    if (!r.ready) mbar_wait(B_FULL + 8 * kb, PH);
    if (r.ts >= 0) TSTAMP(r.ts + kb * 2);
    wg_fence();
    const uint64_t d0 = ((uint64_t)0x40000040u << 32) | ((S_RING + kb * STG_BYTES) >> 4) | (512u << 16);
    #pragma unroll
    for (int kk = 0; kk < 6; kk++) {
      wgmma_rs_n64_t1(acc, a[(kb * 6 + kk) * 4 + 0], a[(kb * 6 + kk) * 4 + 1], a[(kb * 6 + kk) * 4 + 2], a[(kb * 6 + kk) * 4 + 3], d0 + kk * 128, (kb | kk) != 0);
      if (kk == RELPOS && (kb > 0 || !FIRST)) { wg_wait<0>(); arrive_one(B_EMPTY + 8 * ((kb + 5) % 6)); }
      if (kk == SLPOS) slice(kb);
    }
    wg_commit();
    if (!LAST) r.ready = mbar_try_wait(B_FULL + 8 * ((kb + 1) % 6), kb == 5 ? PH ^ 1 : PH);
    if (SLPOS >= 6) slice(kb);
    if (r.ts >= 0) TSTAMP(r.ts + kb * 2 + 1);
    if (RELPOS >= 6 && (kb > 0 || !FIRST)) {
      wg_wait<1>();
      arrive_one(B_EMPTY + 8 * ((kb + 5) % 6));
    }
  }
}

struct CtaId { int m, j; };
__device__ __forceinline__ CtaId cta_id() {
  int bx; asm volatile("mov.u32 %0, %%ctaid.x;" : "=r"(bx));
  bx = __shfl_sync(0xffffffffu, bx, 0);
  return {((bx >> 5) << 2) + ((bx >> 2) & 3), (((bx >> 4) & 1) << 2) + (bx & 3)};
}
__device__ __forceinline__ CtaId cta_id_lane() {
  int bx; asm volatile("mov.u32 %0, %%ctaid.x;" : "=r"(bx));
  return {((bx >> 5) << 2) + ((bx >> 2) & 3), (((bx >> 4) & 1) << 2) + (bx & 3)};
}
struct Maps { CUtensorMap xraw3, x2, xt, xt64, xt8, yt, w1, w3, w2, x8, yt8; };

__global__ void __launch_bounds__(NTHR, 1) k_main(const __grid_constant__ Maps tm, const SsmParams sp, const __nv_bfloat16* __restrict__ dskip,
                                                   __nv_bfloat16* __restrict__ out) {
  extern __shared__ unsigned char smem_raw[];
  const int tid = threadIdx.x, wg = __shfl_sync(0xffffffffu, tid >> 7, 0);
  const int bx = blockIdx.x;
  const bool ffn = bx < NFFN;
  const int m = ((bx >> 5) << 2) + ((bx >> 2) & 3), j = (((bx >> 4) & 1) << 2) + (bx & 3);
  const int d0 = ffn ? bx * 4 : 512 + (bx - NFFN) * 16, npair = ffn ? 1 : 4;
  if (smem_u32(smem_raw) != S_X) return;
  if (tid == 0) TSTAMP(0);
  GSTAMP(0);
  if (wg == 2) {
    asm volatile("setmaxnreg.dec.sync.aligned.u32 24;");
    if (tid == 256) {
      mbar_init(B_RAW, 1);
      asm volatile("fence.mbarrier_init.release.cluster;" ::: "memory");
      if (ffn) { mbar_expect_tx(B_RAW, 18432); tma3d(S_LN, &tm.xraw3, 0, m * 128 + j * 16, 0, B_RAW); }
    } else if (tid >= 288 && tid < 336) {
      const int bi = tid - 288;
      const uint64_t tab = bi < 16 ? 0x88888800111111ull : (bi < 32 ? 0x8440180028011111ull : 0x111188814481440ull);
      const uint32_t c = (uint32_t)(tab >> (4 * (bi & 15))) & 15u;
      if (c) mbar_init(S_BAR + 8 * bi, (bi == 27 && ffn) ? 2 : c);
      asm volatile("fence.mbarrier_init.release.cluster;" ::: "memory");
    }
    bar_sync(0, NTHR);
    const int pw = (tid >> 5) & 3, lane = tid & 31;
    if (pw == 0) {
      if (lane == 0) {
        auto wcoord = [&](int p, const CUtensorMap*& t, int& c0, int& c1) {
          if (p < 18) { t = (p & 1) ? &tm.w3 : &tm.w1; c0 = j * 576 + (p >> 1) * 64; c1 = 0; }
          else { const int s = p - 18; t = &tm.w2; c0 = (s == 0 ? 8 : ((j + s) & 7)) * 64; c1 = j * 576; }
        };
        auto l2pf = [&](int p) {
          const int kb = (m - p * 6) & 15;
          if (kb < 6 && p < 27) { const CUtensorMap* t; int c0, c1; wcoord(p, t, c0, c1);
            asm volatile("cp.async.bulk.prefetch.tensor.2d.L2.global [%0, {%1, %2}];" :: "l"(t), "r"(c0), "r"(c1 + kb * 96) : "memory"); }
        };
        auto wload = [&](int p, int kb0, int kb1) {
          const CUtensorMap* t; int c0, c1; wcoord(p, t, c0, c1);
          #pragma unroll 1
          for (int kb = kb0; kb < kb1; kb++) {
            mbar_expect_tx(B_FULL + 8 * kb, STG_BYTES);
            tma2d(S_RING + kb * STG_BYTES, t, c0, c1 + kb * 96, B_FULL + 8 * kb);
          }
        };
        const unsigned int epoch = cur_epoch();
        if (ffn) {
          mbar_wait(B_RAW, 0);
          wload(0, 0, 3);
          #pragma unroll 1
          for (int p = 0; p <= PFLA; p++) l2pf(p);
        }
        if (ffn) mbar_wait(B_LN2, 0); else __nanosleep(2500);
        #pragma unroll 1
        for (int it = 0; it < 8192; it++) { unsigned int v; asm volatile("ld.acquire.gpu.global.u32 %0, [%1];" : "=r"(v) : "l"(&g_cnt_all) : "memory"); if (v == epoch * NFFN) break; }
        fence_async();
        TSTAMP1(2, 1);
        #pragma unroll 1
        for (int it = 0; it < npair; it++) {
          if (it > 0) mbar_wait(B_CDONE, (it - 1) & 1);
          mbar_expect_tx(B_U, 16384);
          tma2d(S_U, &tm.xt, (d0 + it * 4) * 16, 0, B_U);
        }
        if (ffn) {
          #pragma unroll 1
          for (int w = 0; w < 2; w++) {
            mbar_wait(B_KDONE + 8 * w, 0);
            mbar_expect_tx(B_X + 8 * w, 3 * 16384);
            #pragma unroll 1
            for (int q = 0; q < 3; q++) tma3d(S_X + w * 65536 + q * 16384, &tm.xt64, 0, (w * 3 + q) * 16, m * 8, B_X + 8 * w);
          }
          mbar_wait(B_CDONE, 0);
          wload(0, 3, 6);
          #pragma unroll 1
          for (int w = 0; w < 3; w++) {
            if (w > 0) mbar_wait(B_RDONE - 8 + 8 * w, 0);
            const uint32_t bar = B_X + (w ? 8 + 8 * w : 32);
            mbar_expect_tx(bar, 16384); tma3d(S_X + (w ? 4 * w - 1 : 8) * 16384, &tm.xt64, 0, w ? 80 + 16 * w : 128, m * 8, bar);
          }
          #pragma unroll 1
          for (int p = 1; p < 27; p++) {
            const CUtensorMap* t; int c0, c1; wcoord(p, t, c0, c1);
            #pragma unroll
            for (int kb = 0; kb < 6; kb++) {
              mbar_wait(B_EMPTY + 8 * kb, (p - 1) & 1);
              mbar_expect_tx(B_FULL + 8 * kb, STG_BYTES);
              tma2d(S_RING + kb * STG_BYTES, t, c0, c1 + kb * 96, B_FULL + 8 * kb);
            }
            l2pf(p + PFLA);
          }
        }
      }
      __syncwarp();
    } else {
      const int hw = pw - 1;
      if (tid == 352) { sts32(S_DSK + 196, atomicAdd(&g_ticket, 1) / NCTA + 1); mbar_arrive(B_EP); }
      if (tid == 320) { prefetch_tmap(&tm.xt); prefetch_tmap(&tm.w1); prefetch_tmap(&tm.xt64); prefetch_tmap(&tm.w3); }
      __syncwarp();
      if (hw == 0) {
        const unsigned int epoch = cur_epoch();
        if (ffn) { const uint32_t* dp = (const uint32_t*)dskip; sts32(S_DSK + lane * 4, __ldg(dp + j * 32 + (lane & 24) + ((lane >> 1) & 3) + (lane & 1) * 4)); if (lane < 4) sts32(S_DSK + 128 + lane * 4, __ldg(dp + 256 + j * 4 + lane)); }
        if (ffn && lane == 0) {
          mbar_wait(B_LN, 0);
          TSTAMP1(2, 2);
          asm volatile("cp.async.bulk.global.shared::cta.bulk_group [%0], [%1], %2;" :: "l"(g_xt + (m * 128 + j * 16) * D_), "r"(S_LN + 18432), "r"(18432) : "memory");
          asm volatile("cp.async.bulk.commit_group;" ::: "memory");
          asm volatile("cp.async.bulk.wait_group 0;" ::: "memory");
          TSTAMP1(2, 14);
          fence_async();
          red_add(&g_cnt_all);
          mbar_arrive(B_LN2); TSTAMP1(2, 3);
        }
        __syncwarp();
        if (ffn) {
          #pragma unroll
          for (int i = 0; i < 7; i++) sts128(S_U - 3584 + i * 512 + lane * 16, 0, 0, 0, 0);
          fence_async_smem();
          __syncwarp();
          if (lane == 0) mbar_arrive(B_U);
        }
        mbar_wait(B_CDONE, 0);
        if (ffn) {
          uint4* za = g_acc + (m * 9 + j) * 1024 + lane;
          #pragma unroll 1
          for (int i = 0; i < 32; i++) za[i * 32] = make_uint4(0, 0, 0, 0);
          za = g_acc + (m * 9 + 8) * 1024 + j * 128 + lane;
          #pragma unroll 1
          for (int i = 0; i < 4; i++) za[i * 32] = make_uint4(0, 0, 0, 0);
        }
        __syncwarp();
        if (lane == 0) {
          mbar_wait(B_YDONE, 0);
          fence_gpu(); red_add(ffn ? &g_cnt_y : &g_cnt_ys);
          if (ffn) {
            prefetch_tmap(&tm.x2); prefetch_tmap(&tm.yt); prefetch_tmap(&tm.x8); prefetch_tmap(&tm.xt8); prefetch_tmap(&tm.yt8); prefetch_tmap(&tm.w2);
            flag_wait(&g_cnt_y, epoch * NFFN, 500); fence_async();
            mbar_arrive(B_GO);
            mbar_wait(B_PFREE, 0);
            mbar_expect_tx(B_H, 49152);
            __nanosleep(PACE); tma2d(S_X + 2 * 16384, &tm.x2, j * 64, m * 128, B_H); __nanosleep(PACE); tma3d(S_X + 3 * 16384, &tm.xt64, 0, j * 16, m * 8, B_H); __nanosleep(PACE);
            tma2d(S_X + 4 * 16384, &tm.yt, m * 128, j * 64, B_H); tma2d(S_X + 4 * 16384 + 8192, &tm.yt, m * 128 + 64, j * 64, B_H);
            TSTAMP1(2, 4);
            #pragma unroll 1
            for (int k = 0; k < 3; k++) {
              mbar_wait(B_PUB + 8 * k, 0);
              fence_gpu();
              red_add(&g_cnt_acc[(m * 9 + (k ? (j + 2 * k) & 7 : 8)) * 8]);
              if (k < 2) red_add(&g_cnt_acc[(m * 9 + ((j + 2 * k + 1) & 7)) * 8]);
              TSTAMP1(2, 8 + k);
            }
          }
        }
        __syncwarp();
      }
      if (ffn) {
        if (hw > 0) {
          mbar_wait(B_H, 0);
          #pragma unroll 1
          for (int k = hw - 1; k < 32; k += 2) {
            const uint32_t ln = opaque(lane), r7 = ln & 7, dl = (ln >> 4) * 8 + r7, hf = (k >> 4) * 8192, i = (k >> 2) & 3, wp = k & 3;
            uint32_t x[4], n[4], y[4], k0, k1;
            ldsm_x4t(S_X + 3 * 16384 + hf + wp * 2048 + (i * 4 + (dl >> 2)) * 128 + ((((ln & 3) * 2 + ((ln >> 3) & 1)) ^ ((i * 4 + (dl >> 2)) & 7)) << 4), n[0], n[1], n[2], n[3]);
            ldsm_x4t(S_X + 4 * 16384 + hf + i * 2048 + dl * 128 + (((2 * wp + ((ln >> 3) & 1)) ^ r7) << 4), y[0], y[1], y[2], y[3]);
            ldsm_x4(S_X + 2 * 16384 + hf + wp * 2048 + (ln & 15) * 128 + (((2 * i + (ln >> 4)) ^ r7) << 4), x[0], x[1], x[2], x[3]);
            lds64(S_DSK + i * 32 + (ln & 3) * 8, k0, k1);
            sts128(S_X + 7 * 16384 + k * 512 + ln * 16, add_bf16x2(x[0], add_bf16x2(y[0], mul_bf16x2(n[0], k0))), add_bf16x2(x[1], add_bf16x2(y[1], mul_bf16x2(n[1], k0))),
                   add_bf16x2(x[2], add_bf16x2(y[2], mul_bf16x2(n[2], k1))), add_bf16x2(x[3], add_bf16x2(y[3], mul_bf16x2(n[3], k1))));
          }
          __syncwarp();
          if (lane == 0) {
            mbar_arrive(B_BASE);
            TSTAMP1(2, 5 + hw);
            const CtaId id = cta_id_lane();
            const unsigned int epoch = cur_epoch();
            if (hw == 1) {
              flag_wait(&g_cnt_acc[(id.m * 9 + id.j) * 8], epoch * 4, 100); fence_async();
              mbar_expect_tx(B_R, 16384); bulk_g2s(S_X + 6 * 16384, g_acc + (id.m * 9 + id.j) * 1024, 16384, B_R);
              TSTAMP1(2, 12);
            } else {
              flag_wait(&g_cnt_ys, epoch * (NCTA - NFFN), 300);
              flag_wait(&g_cnt_acc[(id.m * 9 + 8) * 8], epoch * 8, 300); fence_async();
              mbar_expect_tx(B_H8, 8192);
              tma2d(S_X + 8 * 16384, &tm.x8, 512 + id.j * 8, id.m * 128, B_H8); tma3d(S_X + 8 * 16384 + 2048, &tm.xt8, 0, 128 + id.j * 2, id.m * 8, B_H8);
              tma2d(S_X + 8 * 16384 + 4096, &tm.yt8, id.m * 128, 512 + id.j * 8, B_H8); tma2d(S_X + 8 * 16384 + 5120, &tm.yt8, id.m * 128 + 64, 512 + id.j * 8, B_H8);
              bulk_g2s(S_X + 8 * 16384 + 6144, g_acc + (id.m * 9 + 8) * 1024 + id.j * 128, 2048, B_H8);
            }
          }
          __syncwarp();
          if (hw == 2) {
            mbar_wait(B_H8, 0);
            #pragma unroll 1
            for (int k = 0; k < 8; k++) {
              const CtaId id = cta_id();
              const uint32_t ln = opaque(lane);
              uint32_t x0, x1, n0, n1, y0, y1, v0, v1;
              asm volatile("ldmatrix.sync.aligned.m8n8.x2.shared.b16 {%0,%1}, [%2];" : "=r"(x0), "=r"(x1) : "r"(S_X + 8 * 16384 + (k * 16 + (ln & 15)) * 16) : "memory");
              ldsm_x4t((ln & 16) ? S_X + 8 * 16384 + 4096 + (k >> 2) * 1024 + (ln & 7) * 128 + ((((k & 3) * 2 + ((ln >> 3) & 1)) ^ (ln & 7)) << 4)
                                 : S_X + 8 * 16384 + 2048 + (k * 2 + ((ln >> 2) & 1)) * 128 + ((((ln & 3) * 2 + ((ln >> 3) & 1)) ^ ((k * 2 + ((ln >> 2) & 1)) & 7)) << 4), n0, n1, y0, y1);
              const uint32_t k0 = lds32(S_DSK + 128 + (ln & 3) * 4);
              lds64(S_X + 8 * 16384 + 6144 + k * 256 + ln * 8, v0, v1);
              __nv_bfloat16* op = out + ((id.m * 128 + k * 16) * D_ + 512 + id.j * 8) + (ln >> 2) * D_ + (ln & 3) * 2;
              *(uint32_t*)op = add_bf16x2(add_bf16x2(x0, add_bf16x2(y0, mul_bf16x2(n0, k0))), v0);
              *(uint32_t*)(op + 8 * D_) = add_bf16x2(add_bf16x2(x1, add_bf16x2(y1, mul_bf16x2(n1, k0))), v1);
            }
            if (lane == 0) TSTAMP1(2, 13);
          }
        }
      }
    }
  } else {
    asm volatile("setmaxnreg.inc.sync.aligned.u32 240;");
    const ModeRaw mr0 = load_mode(sp, d0 + wg * 2, tid & 127);
    bar_sync(0, NTHR);
    const int t128 = tid & 127, warp = t128 >> 5, lane = tid & 31;
    { const bool g_first = true; (void)g_first; KT(19); }
    ssm_phase(sp, mr0, wg, d0, npair, ffn ? m * 128 + j * 16 : -1, t128);
    TSTAMP(9); GSTAMP(1);
    if (ffn) {
    uint32_t a[144];
    float accG[32], accU[32];
    Ring r{false, -1, 0};
    const uint32_t park = S_X + wg * 8192 + t128 * 16;
    auto nop = [](int) {};
    auto silu_slice = [&](int kb, int t) {
      if (kb >= 1 && kb <= 4) {
        const int i0 = (kb - 1) * 8;
        sts128(park + t * 16384 + (kb - 1) * 2048, pack_bf16(silu_f(accG[i0]), silu_f(accG[i0 + 1])), pack_bf16(silu_f(accG[i0 + 2]), silu_f(accG[i0 + 3])),
               pack_bf16(accG[i0 + 4], accG[i0 + 5]), pack_bf16(accG[i0 + 6], accG[i0 + 7]));
      }
    };
    auto mul_unit = [&](int i, int t, uint32_t& h0, uint32_t& h1, uint32_t& h2, uint32_t& h3) {
      uint32_t s0, s1, g2, g3; const int i0 = i * 8;
      lds128(park + t * 16384 + i * 2048, s0, s1, g2, g3);
      h0 = mul_bf16x2(s0, pack_bf16(accU[i0], accU[i0 + 1])); h1 = mul_bf16x2(s1, pack_bf16(accU[i0 + 2], accU[i0 + 3]));
      h2 = mul_bf16x2(pack_bf16(silu_f(bf_lo(g2)), silu_f(bf_hi(g2))), pack_bf16(accU[i0 + 4], accU[i0 + 5]));
      h3 = mul_bf16x2(pack_bf16(silu_f(bf_lo(g3)), silu_f(bf_hi(g3))), pack_bf16(accU[i0 + 6], accU[i0 + 7]));
    };
    {
      const uint32_t xrow = (lane >> 4) * 2 + ((lane >> 2) & 1);
      const uint32_t rbase = S_X + wg * 8192 + warp * 2048 + xrow * 128 + ((((lane & 3) * 2 + ((lane >> 3) & 1)) ^ xrow) << 4);
      auto ldx = [&](int kb) {
          if (kb == 0) mbar_wait(B_X, 0);
          if (kb == 2) mbar_wait(B_X + 8, 0);
          if (kb == 4) { mbar_wait(B_X + 16, 0); mbar_wait(B_X + 24, 0); }
          if (kb == 5) mbar_wait(B_X + 32, 0);
          #pragma unroll
          for (int kk = 0; kk < 6; kk++) {
            const int ks = kb * 6 + kk;
            ldsm_x4t((rbase ^ ((ks & 1) * 64)) + xslot(ks >> 2) * 16384 + (ks & 3) * 512, a[ks * 4 + 0], a[ks * 4 + 1], a[ks * 4 + 2], a[ks * 4 + 3]);
          }
          if (kb == 0) TSTAMP(1);
        };
      run_pass<0, 0, 5, true>(accG, a, r, ldx, nop);
      ldx(5);
    }
    bar_sync(2 + wg, 128);
    auto reload = [&](int grp, int on) {
      #pragma unroll
      for (int i = 0; i < 6; i++) {
        const int q = grp * 6 + i;
        if (q < 32) asm volatile("{\n.reg .pred p;\nsetp.ne.b32 p, %5, 0;\n@p ld.shared.v4.b32 {%0,%1,%2,%3}, [%4];\n}\n"
                                 : "+r"(a[q * 4]), "+r"(a[q * 4 + 1]), "+r"(a[q * 4 + 2]), "+r"(a[q * 4 + 3]) : "r"(park + (q >> 2) * 16384 + (q & 3) * 2048), "r"(on) : "memory");
      }
    };
    #pragma unroll 1
    for (int t = 0; t < 9; t++) {
      run_pass<0, 5, 6>(accG, a, r, nop, nop);
      run_pass<1>(accU, a, r, nop, [&](int kb) { silu_slice(kb, t); if (kb >= 2) reload(kb - 2, t == 8); });
      run_pass<0, 0, 5>(accG, a, r, nop, [&](int kb) {
        if (kb <= 1) reload(4 + kb, t == 8);
        if (kb >= 1) {
          uint32_t h0, h1, h2, h3; mul_unit(kb - 1, t, h0, h1, h2, h3);
          sts128(park + t * 16384 + (kb - 1) * 2048, h0, h1, h2, h3);
          asm volatile("{\n.reg .pred p;\nsetp.ne.b32 p, %8, 0;\n@p mov.b32 %0, %4;\n@p mov.b32 %1, %5;\n@p mov.b32 %2, %6;\n@p mov.b32 %3, %7;\n}\n"
                       : "+r"(a[124 + kb * 4]), "+r"(a[125 + kb * 4]), "+r"(a[126 + kb * 4]), "+r"(a[127 + kb * 4]) : "r"(h0), "r"(h1), "r"(h2), "r"(h3), "r"((int)(t == 8)));
        } });
      r.ts = -1;
      if (t == 0) { TSTAMP(2); GSTAMP(2); }
      if (t == 3) { TSTAMP(11); GSTAMP(6); }
      if (t == 7) { TSTAMP(3); GSTAMP(3); }
    }
    TSTAMP(4);
    fence_async_smem(); __syncwarp(); arrive_one(B_PFREE);
    const uint32_t tag = opaque(cur_epoch() & 1);
    const CtaId id2 = cta_id(); const int m = id2.m, j = id2.j;
    const uint32_t pk = park - S_X;
    auto store_vec = [&](const float* acc, int t, int i, bool may0) {
      uint32_t w0 = pack_bf16(acc[i * 8], acc[i * 8 + 1]), w1 = pack_bf16(acc[i * 8 + 2], acc[i * 8 + 3]), w2 = pack_bf16(acc[i * 8 + 4], acc[i * 8 + 5]), w3 = pack_bf16(acc[i * 8 + 6], acc[i * 8 + 7]);
      if (may0 && __builtin_expect(t == 0, 0)) {
        if (i == 0) mbar_wait(B_GO, 0);
        const uint32_t pq = opaque(pk);
        char* dst = (char*)g_acc + (size_t)(m * 9 + 8) * 16384 + i * 4096 + (((pq >> 1) & 1023) | ((pq >> 3) & 1024));
        asm volatile("red.relaxed.gpu.global.add.noftz.v2.bf16x2 [%0], {%1,%2};" :: "l"(dst), "r"(w0), "r"(w1) : "memory");
        asm volatile("red.relaxed.gpu.global.add.noftz.v2.bf16x2 [%0], {%1,%2};" :: "l"(dst + 2048), "r"(w2), "r"(w3) : "memory");
      } else {
        const int blk = (j + t) & 7;
        const char* base = t >= 5 ? (const char*)g_part + (size_t)((m * 8 + blk) * 3 + t - 5) * 16384 : (const char*)g_acc + (size_t)(m * 9 + blk) * 16384;
        asm volatile("{\n.reg .pred p;\n.reg .b32 a, b, c, d;\nsetp.ge.s32 p, %6, 5;\n"
                     "lop3.b32 a, %1, -2, %5, 0xEA;\nlop3.b32 b, %2, -2, %5, 0xEA;\nlop3.b32 c, %3, -2, %5, 0xEA;\nlop3.b32 d, %4, -2, %5, 0xEA;\n"
                     "@p st.relaxed.gpu.global.v4.b32 [%0], {a,b,c,d};\n@!p red.relaxed.gpu.global.add.noftz.v4.bf16x2 [%0], {%1,%2,%3,%4};\n}\n"
                     :: "l"(base + i * 2048 + pk), "r"(w0), "r"(w1), "r"(w2), "r"(w3), "r"(tag), "r"(t) : "memory");
        if (i == 3) { __syncwarp(); asm volatile("{\n.reg .pred p, q;\nelect.sync _|p, 0xffffffff;\nsetp.ne.and.b32 q, %1, 0, p;\n@q mbarrier.arrive.shared::cta.b64 _, [%0];\n}\n" :: "r"(B_PUB + 8 * (t >> 1)), "r"((int)(t < 5 && t != 2)) : "memory"); }
      }
    };
    auto own_part = [&](int s) { return (const char*)g_part + (size_t)((m * 8 + j) * 3 + s - 5) * 16384 + pk; };
    auto fetch = [&](int s) {
      const char* src = own_part(s);
      #pragma unroll
      for (int i = 0; i < 4; i++) cp_async16(park + (s & 1) * 16384 + i * 2048, src + i * 2048);
      cp_commit();
    };
    uint32_t missing = 0;
    auto final_vec = [&](int i) {
      uint32_t v[4], f[4], b[4];
      lds128(park + 16384 + i * 2048, v[0], v[1], v[2], v[3]);
      lds128(park + 6 * 16384 + i * 2048, f[0], f[1], f[2], f[3]); lds128(park + 7 * 16384 + i * 2048, b[0], b[1], b[2], b[3]);
      if (tag_bad(v[0], v[1], v[2], v[3], tag)) { missing |= 1u << i; v[0] = v[1] = v[2] = v[3] = 0; }
      #pragma unroll
      for (int e = 0; e < 4; e++) { const uint32_t t = add_bf16x2(f[e], v[e]); accU[i * 8 + 2 * e] = bf_lo(t) + bf_lo(b[e]); accU[i * 8 + 2 * e + 1] = bf_hi(t) + bf_hi(b[e]); }
    };
    #pragma unroll 1
    for (int u = 1; u < 7; u += 2) {
      run_pass<0, 5, 6>(accG, a, r, nop, nop);
      run_pass<1>(accU, a, r, nop, [&](int kb) { if (kb >= 1 && kb <= 4) store_vec(accG, u - 1, kb - 1, true); });
      run_pass<0, 0, 5>(accG, a, r, nop, [&](int kb) { if (kb >= 1) store_vec(accU, u, kb - 1, false); });
    }
    TSTAMP(5); GSTAMP(4);
    run_pass<0, 5, 6>(accG, a, r, nop, nop);
    run_pass<1>(accU, a, r, nop, [&](int kb) { if (kb >= 1 && kb <= 4) store_vec(accG, 6, kb - 1, false); if (kb == 5) fetch(5); });
    run_pass<0, 0, 5>(accG, a, r, nop, [&](int kb) {
      if (kb == 1) { store_vec(accU, 7, 0, false); store_vec(accU, 7, 1, false); store_vec(accU, 7, 2, false); store_vec(accU, 7, 3, false); fetch(6); }
      if (kb == 2) { mbar_wait(B_BASE, 0); mbar_wait(B_R, 0); cp_wait<1>(); }
      if (kb >= 2) final_vec(kb - 2); });
    r.ts = -1;
    {
      const uint4* src = (const uint4*)own_part(7);
      uint32_t v[16];
      run_pass<0, 5, 6, false, true>(accG, a, r, nop, [&](int) {
        final_vec(3);
        #pragma unroll
        for (int i = 0; i < 4; i++) ld_relaxed_v4(src + i * 128, v[i * 4], v[i * 4 + 1], v[i * 4 + 2], v[i * 4 + 3]);
      });
      cp_wait<0>();
      #pragma unroll
      for (int i = 0; i < 4; i++) {
        uint32_t w[4]; lds128(park + i * 2048, w[0], w[1], w[2], w[3]);
        if (tag_bad(w[0], w[1], w[2], w[3], tag)) { missing |= 16u << i; w[0] = w[1] = w[2] = w[3] = 0; }
        if (tag_bad(v[i * 4], v[i * 4 + 1], v[i * 4 + 2], v[i * 4 + 3], tag)) { missing |= 256u << i; v[i * 4] = v[i * 4 + 1] = v[i * 4 + 2] = v[i * 4 + 3] = 0; }
        add_vec(accU + i * 8, add_bf16x2(v[i * 4], w[0]), add_bf16x2(v[i * 4 + 1], w[1]), add_bf16x2(v[i * 4 + 2], w[2]), add_bf16x2(v[i * 4 + 3], w[3]));
      }
      if (missing) {
        #pragma unroll
        for (int i = 0; i < 4; i++) {
          #pragma unroll 1
          for (int s = 0; s < 3; s++)
            if (missing >> (4 * s + i) & 1) { uint32_t v0, v1, v2, v3; poll_v4((const uint4*)own_part(5 + s) + i * 128, v0, v1, v2, v3, tag); add_vec(accU + i * 8, v0, v1, v2, v3); }
        }
      }
      __syncwarp();
      wg_wait<0>();
      TSTAMP(6);
      #pragma unroll
      for (int i = 0; i < 32; i++) accU[i] += accG[i];
      const uint32_t pq = opaque(pk); const int lane = (pq >> 4) & 31, warp = (pq >> 9) & 3, wg = pq >> 13;
      const uint32_t stg = S_X + 4 * 16384 + wg * 8192 + warp * 2048;
      #pragma unroll
      for (int i = 0; i < 4; i++) {
        const int row = (lane & 7) + ((lane >> 3) & 1) * 8, chunk = 2 * i + (lane >> 4);
        asm volatile("stmatrix.sync.aligned.m8n8.x4.shared.b16 [%0], {%1,%2,%3,%4};" :: "r"(stg + row * 128 + ((chunk ^ (row & 7)) << 4)),
                     "r"(pack_bf16(accU[i * 8], accU[i * 8 + 1])), "r"(pack_bf16(accU[i * 8 + 2], accU[i * 8 + 3])), "r"(pack_bf16(accU[i * 8 + 4], accU[i * 8 + 5])), "r"(pack_bf16(accU[i * 8 + 6], accU[i * 8 + 7])) : "memory");
      }
      __syncwarp();
      TSTAMP(8);
      #pragma unroll
      for (int i = 0; i < 4; i++) {
        const int row = i * 4 + (lane >> 3), chunk = lane & 7;
        uint32_t o0, o1, o2, o3; lds128(stg + row * 128 + ((chunk ^ (row & 7)) << 4), o0, o1, o2, o3);
        *(uint4*)(out + (m * 128 + wg * 64 + warp * 16 + row) * D_ + j * 64 + chunk * 8) = make_uint4(o0, o1, o2, o3);
      }
    }
    }
    TSTAMP(7);
  }
}

typedef CUresult (*EncFn)(CUtensorMap*, CUtensorMapDataType, cuuint32_t, void*, const cuuint64_t*, const cuuint64_t*, const cuuint32_t*, const cuuint32_t*, CUtensorMapInterleave, CUtensorMapSwizzle, CUtensorMapL2promotion, CUtensorMapFloatOOBfill);
static void enc(EncFn f, CUtensorMap* tm, const void* base, int rank, uint64_t d0, uint64_t d1, uint64_t d2, uint64_t s1, uint64_t s2, uint32_t b0, uint32_t b1, uint32_t b2, CUtensorMapSwizzle sw) {
  cuuint64_t dims[3] = {d0, d1, d2}; cuuint64_t strides[2] = {s1, s2}; cuuint32_t box[3] = {b0, b1, b2}; cuuint32_t es[3] = {1, 1, 1};
  CUresult r = f(tm, CU_TENSOR_MAP_DATA_TYPE_BFLOAT16, rank, (void*)base, dims, strides, box, es, CU_TENSOR_MAP_INTERLEAVE_NONE, sw, CU_TENSOR_MAP_L2_PROMOTION_L2_128B, CU_TENSOR_MAP_FLOAT_OOB_FILL_NONE);
  if (r != CUDA_SUCCESS) fprintf(stderr, "tensor map encode failed %d\n", (int)r);
}

extern "C" void kernel_launch(void* const* d_in, const int* in_sizes, int n_in, void* d_out, int out_size) {
  static bool init = false;
  static Maps tm;
  if (!init) {
    void* fn = nullptr; cudaDriverEntryPointQueryResult st;
    cudaGetDriverEntryPoint("cuTensorMapEncodeTiled", &fn, cudaEnableDefault, &st);
    EncFn f = (EncFn)fn;
    void *xt, *yt; cudaGetSymbolAddress(&xt, g_xt); cudaGetSymbolAddress(&yt, g_yt);
    const CUtensorMapSwizzle S128 = CU_TENSOR_MAP_SWIZZLE_128B;
    enc(f, &tm.xraw3, d_in[0], 3, 64, L_, 9, D_ * 2, 128, 64, 16, 9, S128);
    enc(f, &tm.x2, d_in[0], 2, D_, L_, 1, D_ * 2, 0, 64, 128, 1, S128);
    enc(f, &tm.xt64, xt, 3, 64, D_ / 4, 128, 128, 32 * D_, 64, 16, 8, S128);
    enc(f, &tm.xt8, xt, 3, 64, D_ / 4, 128, 128, 32 * D_, 64, 2, 8, S128);
    enc(f, &tm.xt, xt, 2, 16 * D_, 128, 1, 32 * D_, 0, 64, 128, 1, S128);
    enc(f, &tm.yt, yt, 2, L_, D_, 1, L_ * 2, 0, 64, 64, 1, S128);
    enc(f, &tm.w1, d_in[10], 2, F_, D_, 1, F_ * 2, 0, 64, 96, 1, S128);
    enc(f, &tm.w3, d_in[11], 2, F_, D_, 1, F_ * 2, 0, 64, 96, 1, S128);
    enc(f, &tm.w2, d_in[12], 2, D_, F_, 1, D_ * 2, 0, 64, 96, 1, S128);
    enc(f, &tm.x8, d_in[0], 2, D_, L_, 1, D_ * 2, 0, 8, 128, 1, CU_TENSOR_MAP_SWIZZLE_NONE);
    enc(f, &tm.yt8, yt, 2, L_, D_, 1, L_ * 2, 0, 64, 8, 1, S128);
    cudaFuncSetAttribute(k_main, cudaFuncAttributeMaxDynamicSharedMemorySize, SMEM_BYTES);
    init = true;
  }
  SsmParams sp{(const __nv_bfloat16*)d_in[1], (const __nv_bfloat16*)d_in[2], (const __nv_bfloat16*)d_in[3], (const __nv_bfloat16*)d_in[4],
               (const __nv_bfloat16*)d_in[5], (const __nv_bfloat16*)d_in[6], (const __nv_bfloat16*)d_in[7]};
  k_main<<<NCTA, NTHR, SMEM_BYTES>>>(tm, sp, (const __nv_bfloat16*)d_in[8], (__nv_bfloat16*)d_out);
}
```

```cpp
#include <cuda_runtime.h>
#include <cuda.h>
#include <cuda_bf16.h>
#include <stdint.h>
#include <stdio.h>

__device__ __forceinline__ void wgmma_rs_n64_t1(float* d, uint32_t a0, uint32_t a1, uint32_t a2, uint32_t a3, uint64_t descB, int scaleD) {
  asm volatile("{\n.reg .pred p;\nsetp.ne.b32 p, %37, 0;\n"
    "wgmma.mma_async.sync.aligned.m64n64k16.f32.bf16.bf16 {%0,%1,%2,%3,%4,%5,%6,%7,%8,%9,%10,%11,%12,%13,%14,%15,%16,%17,%18,%19,%20,%21,%22,%23,%24,%25,%26,%27,%28,%29,%30,%31}, {%32,%33,%34,%35}, %36, p, 1, 1, 1;\n}\n"
    : "+f"(d[0]), "+f"(d[1]), "+f"(d[2]), "+f"(d[3]), "+f"(d[4]), "+f"(d[5]), "+f"(d[6]), "+f"(d[7]), "+f"(d[8]), "+f"(d[9]), "+f"(d[10]), "+f"(d[11]), "+f"(d[12]), "+f"(d[13]), "+f"(d[14]), "+f"(d[15]), "+f"(d[16]), "+f"(d[17]), "+f"(d[18]), "+f"(d[19]), "+f"(d[20]), "+f"(d[21]), "+f"(d[22]), "+f"(d[23]), "+f"(d[24]), "+f"(d[25]), "+f"(d[26]), "+f"(d[27]), "+f"(d[28]), "+f"(d[29]), "+f"(d[30]), "+f"(d[31])
    : "r"(a0), "r"(a1), "r"(a2), "r"(a3), "l"(descB), "r"(scaleD));
}
__device__ __forceinline__ void wgmma_ss_n48_t0(float* d, uint64_t descA, uint64_t descB, int scaleD) {
  asm volatile("{\n.reg .pred p;\nsetp.ne.b32 p, %26, 0;\n"
    "wgmma.mma_async.sync.aligned.m64n48k16.f32.bf16.bf16 {%0,%1,%2,%3,%4,%5,%6,%7,%8,%9,%10,%11,%12,%13,%14,%15,%16,%17,%18,%19,%20,%21,%22,%23}, %24, %25, p, 1, 1, 0, 0;\n}\n"
    : "+f"(d[0]), "+f"(d[1]), "+f"(d[2]), "+f"(d[3]), "+f"(d[4]), "+f"(d[5]), "+f"(d[6]), "+f"(d[7]), "+f"(d[8]), "+f"(d[9]), "+f"(d[10]), "+f"(d[11]), "+f"(d[12]), "+f"(d[13]), "+f"(d[14]), "+f"(d[15]), "+f"(d[16]), "+f"(d[17]), "+f"(d[18]), "+f"(d[19]), "+f"(d[20]), "+f"(d[21]), "+f"(d[22]), "+f"(d[23])
    : "l"(descA), "l"(descB), "r"(scaleD));
}
__device__ __forceinline__ void wgmma_rs_n32_t0(float* d, uint32_t a0, uint32_t a1, uint32_t a2, uint32_t a3, uint64_t descB, int scaleD) {
  asm volatile("{\n.reg .pred p;\nsetp.ne.b32 p, %21, 0;\n"
    "wgmma.mma_async.sync.aligned.m64n32k16.f32.bf16.bf16 {%0,%1,%2,%3,%4,%5,%6,%7,%8,%9,%10,%11,%12,%13,%14,%15}, {%16,%17,%18,%19}, %20, p, 1, 1, 0;\n}\n"
    : "+f"(d[0]), "+f"(d[1]), "+f"(d[2]), "+f"(d[3]), "+f"(d[4]), "+f"(d[5]), "+f"(d[6]), "+f"(d[7]), "+f"(d[8]), "+f"(d[9]), "+f"(d[10]), "+f"(d[11]), "+f"(d[12]), "+f"(d[13]), "+f"(d[14]), "+f"(d[15])
    : "r"(a0), "r"(a1), "r"(a2), "r"(a3), "l"(descB), "r"(scaleD));
}

#define PFLA 6
#define SLPOS 2
#define INCFIRST
#define TANHSILU
#define MAPMODE 0
constexpr int L_ = 2048, D_ = 576, F_ = 4608;
constexpr int NFFN = 128, NCTA = 132, NTHR = 384;
constexpr int STG_BYTES = 12288;
constexpr uint32_t S_X = 1024;
constexpr uint32_t S_RING = S_X + 147456;
constexpr uint32_t S_MISC = S_RING + 6 * STG_BYTES;
constexpr uint32_t S_BAR = S_MISC + 8320, S_DSK = S_BAR + 512, S_DUMMY = S_DSK + 256;
constexpr int SMEM_BYTES = S_DUMMY + 256 + 768 - 1024;
constexpr uint32_t B_FULL = S_BAR, B_EMPTY = S_BAR + 64, B_X = S_BAR + 128  , B_PFREE = S_BAR + 176, B_BASE = S_BAR + 184  ,
                   B_RAW = S_BAR + 200, B_LN = S_BAR + 208, B_U = S_BAR + 216  , B_KDONE = S_BAR + 232  , B_CDONE = S_BAR + 248  ,
                   B_RDONE = S_BAR + 264  , B_H = S_BAR + 280, B_YDONE = S_BAR + 288, B_PP = S_BAR + 296  , B_GO = S_BAR + 312, B_PUB = S_BAR + 320  , B_R = S_BAR + 344, B_H8 = S_BAR + 352, B_EP = S_BAR + 360, B_LN2 = S_BAR + 368;
constexpr uint32_t S_LN = S_RING + 3 * STG_BYTES;
constexpr uint32_t S_U = S_LN + 20480;
__device__ __forceinline__ uint32_t s_w_of(int ch) { return ch < 2 ? S_LN + ch * 8256 : (ch == 2 ? S_X + 8 * 16384 : S_MISC); }
__host__ __device__ constexpr int xslot(int kb) { return kb < 3 ? kb : (kb < 6 ? kb + 1 : (kb == 6 ? 3 : kb)); }

__device__ __nv_bfloat16 g_xt[D_ * L_];
__device__ __nv_bfloat16 g_yt[D_ * L_];
__device__ uint4 g_part[16 * 8 * 3 * 1024];
__device__ uint4 g_acc[16 * 9 * 1024];
__device__ unsigned int g_cnt_acc[16 * 9 * 8];
__device__ unsigned int g_ticket, g_cnt_all, g_cnt_y, g_cnt_ys;
#define TSTAMP(i)
#define GSTAMP(i)
#define TSTAMP1(w, i)

#define CT(i)
#define KT(i)
__device__ __forceinline__ uint32_t smem_u32(const void* p) { return (uint32_t)__cvta_generic_to_shared(p); }
__device__ __forceinline__ void mbar_init(uint32_t bar, uint32_t cnt) { asm volatile("mbarrier.init.shared::cta.b64 [%0], %1;" :: "r"(bar), "r"(cnt)); }
__device__ __forceinline__ void mbar_expect_tx(uint32_t bar, uint32_t bytes) { asm volatile("mbarrier.arrive.expect_tx.shared::cta.b64 _, [%0], %1;" :: "r"(bar), "r"(bytes) : "memory"); }
__device__ __forceinline__ void mbar_arrive(uint32_t bar) { asm volatile("mbarrier.arrive.shared::cta.b64 _, [%0];" :: "r"(bar) : "memory"); }
__device__ __forceinline__ bool mbar_try_wait(uint32_t bar, uint32_t parity) {
  uint32_t ok;
  asm volatile("{\n.reg .pred p;\nmbarrier.try_wait.parity.shared::cta.b64 p, [%1], %2;\nselp.u32 %0, 1, 0, p;\n}\n" : "=r"(ok) : "r"(bar), "r"(parity) : "memory");
  return ok;
}
__device__ __forceinline__ void mbar_wait(uint32_t bar, uint32_t parity) {
  asm volatile("{\n.reg .pred p;\n.reg .u32 c;\nmov.u32 c, 0;\n"
               "WAIT_LOOP:\nmbarrier.try_wait.parity.shared::cta.b64 p, [%0], %1;\nadd.u32 c, c, 1;\n@!p setp.gt.u32 p, c, 1024;\n@!p bra WAIT_LOOP;\n}\n" :: "r"(bar), "r"(parity) : "memory");
}
__device__ __forceinline__ void mbar_spin(uint32_t bar, uint32_t parity) {
  asm volatile("{\n.reg .pred p;\n.reg .u32 c;\nmov.u32 c, 0;\n"
               "SPIN_LOOP:\nmbarrier.test_wait.parity.shared::cta.b64 p, [%0], %1;\nadd.u32 c, c, 1;\n@!p setp.gt.u32 p, c, 0x100000;\n@!p bra SPIN_LOOP;\n}\n" :: "r"(bar), "r"(parity) : "memory");
}
__device__ __forceinline__ void flag_wait(const unsigned int* f, unsigned int val, unsigned int ns) {
  unsigned int v;
  #pragma unroll 1
  for (int it = 0; it < 16384; it++) {
    asm volatile("ld.relaxed.gpu.global.u32 %0, [%1];" : "=r"(v) : "l"(f) : "memory");
    if (v == val) break;
    __nanosleep(ns);
  }
  asm volatile("ld.acquire.gpu.global.u32 %0, [%1];" : "=r"(v) : "l"(f) : "memory");
}
__device__ __forceinline__ void red_add(unsigned int* p) { asm volatile("red.relaxed.gpu.global.add.u32 [%0], 1;" :: "l"(p) : "memory"); }
__device__ __forceinline__ void fence_gpu() { asm volatile("fence.acq_rel.gpu;" ::: "memory"); }
__device__ __forceinline__ void fence_async() { asm volatile("fence.proxy.async.global;" ::: "memory"); }
__device__ __forceinline__ void fence_async_smem() { asm volatile("fence.proxy.async.shared::cta;" ::: "memory"); }
__device__ __forceinline__ unsigned int cur_epoch() { mbar_wait(B_EP, 0); unsigned int v; asm volatile("ld.shared.b32 %0, [%1];" : "=r"(v) : "r"(S_DSK + 196) : "memory"); return v; }
__device__ __forceinline__ void tma2d(uint32_t dst, const CUtensorMap* tm, int c0, int c1, uint32_t bar) {
  asm volatile("cp.async.bulk.tensor.2d.shared::cluster.global.mbarrier::complete_tx::bytes [%0], [%1, {%3, %4}], [%2];" :: "r"(dst), "l"(tm), "r"(bar), "r"(c0), "r"(c1) : "memory");
}
__device__ __forceinline__ void tma3d(uint32_t dst, const CUtensorMap* tm, int c0, int c1, int c2, uint32_t bar) {
  asm volatile("cp.async.bulk.tensor.3d.shared::cluster.global.mbarrier::complete_tx::bytes [%0], [%1, {%3, %4, %5}], [%2];" :: "r"(dst), "l"(tm), "r"(bar), "r"(c0), "r"(c1), "r"(c2) : "memory");
}
__device__ __forceinline__ void bulk_g2s(uint32_t dst, const void* src, uint32_t bytes, uint32_t bar) {
  asm volatile("cp.async.bulk.shared::cluster.global.mbarrier::complete_tx::bytes [%0], [%1], %2, [%3];" :: "r"(dst), "l"(src), "r"(bytes), "r"(bar) : "memory");
}
__device__ __forceinline__ void prefetch_tmap(const CUtensorMap* tm) { asm volatile("prefetch.tensormap [%0];" :: "l"(tm) : "memory"); }
__device__ __forceinline__ void wg_fence() { asm volatile("wgmma.fence.sync.aligned;" ::: "memory"); }
__device__ __forceinline__ void wg_commit() { asm volatile("wgmma.commit_group.sync.aligned;" ::: "memory"); }
template <int N> __device__ __forceinline__ void wg_wait() { asm volatile("wgmma.wait_group.sync.aligned %0;" :: "n"(N) : "memory"); }
__device__ __forceinline__ void bar_sync(int id, int n) { asm volatile("bar.sync %0, %1;" :: "r"(id), "r"(n) : "memory"); }
__device__ __forceinline__ void bar_arrive(int id, int n) { asm volatile("bar.arrive %0, %1;" :: "r"(id), "r"(n) : "memory"); }
__device__ __forceinline__ uint32_t pack_bf16(float lo, float hi) { uint32_t r; asm("cvt.rn.bf16x2.f32 %0, %1, %2;" : "=r"(r) : "f"(hi), "f"(lo)); return r; }
__device__ __forceinline__ float bf_lo(uint32_t v) { return __uint_as_float(v << 16); }
__device__ __forceinline__ float bf_hi(uint32_t v) { return __uint_as_float(v & 0xFFFF0000u); }
__device__ __forceinline__ float bf_round(float v) { return bf_lo(pack_bf16(v, v)); }
__device__ __forceinline__ uint32_t mul_bf16x2(uint32_t a, uint32_t b) { uint32_t r; asm("mul.rn.bf16x2 %0, %1, %2;" : "=r"(r) : "r"(a), "r"(b)); return r; }
__device__ __forceinline__ uint32_t add_bf16x2(uint32_t a, uint32_t b) { uint32_t r; asm("add.rn.bf16x2 %0, %1, %2;" : "=r"(r) : "r"(a), "r"(b)); return r; }
__device__ __forceinline__ uint32_t sub_bf16x2(uint32_t a, uint32_t b) { uint32_t r; asm("sub.rn.bf16x2 %0, %1, %2;" : "=r"(r) : "r"(a), "r"(b)); return r; }
__device__ __forceinline__ void ldsm_x4(uint32_t addr, uint32_t& r0, uint32_t& r1, uint32_t& r2, uint32_t& r3) {
  asm volatile("ldmatrix.sync.aligned.m8n8.x4.shared.b16 {%0,%1,%2,%3}, [%4];" : "=r"(r0), "=r"(r1), "=r"(r2), "=r"(r3) : "r"(addr) : "memory");
}
__device__ __forceinline__ void ldsm_x4t(uint32_t addr, uint32_t& r0, uint32_t& r1, uint32_t& r2, uint32_t& r3) {
  asm volatile("ldmatrix.sync.aligned.m8n8.x4.trans.shared.b16 {%0,%1,%2,%3}, [%4];" : "=r"(r0), "=r"(r1), "=r"(r2), "=r"(r3) : "r"(addr) : "memory");
}
__device__ __forceinline__ float silu_f(float g) {
  const float hh = 0.5f * g; float th; asm("tanh.approx.f32 %0, %1;" : "=f"(th) : "f"(hh)); return fmaf(hh, th, hh);
  float e; asm("ex2.approx.ftz.f32 %0, %1;" : "=f"(e) : "f"(g * -1.4426950408889634f));
  float r; asm("rcp.approx.ftz.f32 %0, %1;" : "=f"(r) : "f"(1.0f + e));
  return g * r;
}
__device__ __forceinline__ void sts128(uint32_t addr, uint32_t a, uint32_t b, uint32_t c, uint32_t d) { asm volatile("st.shared.v4.b32 [%0], {%1,%2,%3,%4};" :: "r"(addr), "r"(a), "r"(b), "r"(c), "r"(d) : "memory"); }
__device__ __forceinline__ void sts64(uint32_t addr, uint32_t a, uint32_t b) { asm volatile("st.shared.v2.b32 [%0], {%1,%2};" :: "r"(addr), "r"(a), "r"(b) : "memory"); }
__device__ __forceinline__ void sts32(uint32_t addr, uint32_t a) { asm volatile("st.shared.b32 [%0], %1;" :: "r"(addr), "r"(a) : "memory"); }
__device__ __forceinline__ void lds128(uint32_t addr, uint32_t& a, uint32_t& b, uint32_t& c, uint32_t& d) { asm volatile("ld.shared.v4.b32 {%0,%1,%2,%3}, [%4];" : "=r"(a), "=r"(b), "=r"(c), "=r"(d) : "r"(addr) : "memory"); }
__device__ __forceinline__ void lds64(uint32_t addr, uint32_t& a, uint32_t& b) { asm volatile("ld.shared.v2.b32 {%0,%1}, [%2];" : "=r"(a), "=r"(b) : "r"(addr) : "memory"); }
__device__ __forceinline__ uint32_t lds32(uint32_t addr) { uint32_t a; asm volatile("ld.shared.b32 %0, [%1];" : "=r"(a) : "r"(addr) : "memory"); return a; }
__device__ __forceinline__ float ldsf(uint32_t addr) { float a; asm volatile("ld.shared.f32 %0, [%1];" : "=f"(a) : "r"(addr) : "memory"); return a; }
__device__ __forceinline__ uint32_t opaque(uint32_t v) { uint32_t r; asm volatile("mov.b32 %0, %1;" : "=r"(r) : "r"(v)); return r; }
__device__ __forceinline__ void cp_async16(uint32_t dst, const void* src) { asm volatile("cp.async.cg.shared.global [%0], [%1], 16;" :: "r"(dst), "l"(src) : "memory"); }
__device__ __forceinline__ void cp_commit() { asm volatile("cp.async.commit_group;" ::: "memory"); }
template <int N> __device__ __forceinline__ void cp_wait() { asm volatile("cp.async.wait_group %0;" :: "n"(N) : "memory"); }
__device__ __forceinline__ void st_relaxed_v4(uint4* p, uint32_t a, uint32_t b, uint32_t c, uint32_t d) {
  asm volatile("st.relaxed.gpu.global.v4.b32 [%0], {%1,%2,%3,%4};" :: "l"(p), "r"(a), "r"(b), "r"(c), "r"(d) : "memory");
}
__device__ __forceinline__ void ld_relaxed_v4(const uint4* p, uint32_t& a, uint32_t& b, uint32_t& c, uint32_t& d) {
  asm volatile("ld.relaxed.gpu.global.v4.b32 {%0,%1,%2,%3}, [%4];" : "=r"(a), "=r"(b), "=r"(c), "=r"(d) : "l"(p) : "memory");
}
__device__ __forceinline__ bool tag_bad(uint32_t a, uint32_t b, uint32_t c, uint32_t d, uint32_t tag) { return (((a ^ tag) | (b ^ tag) | (c ^ tag) | (d ^ tag)) & 1u) != 0; }
__device__ __forceinline__ void poll_v4(const uint4* p, uint32_t& a, uint32_t& b, uint32_t& c, uint32_t& d, uint32_t tag) {
  int it = 0;
  do { ld_relaxed_v4(p, a, b, c, d); } while (tag_bad(a, b, c, d, tag) && ++it < 4096);
}
__device__ __forceinline__ void add_vec(float* f, uint32_t v0, uint32_t v1, uint32_t v2, uint32_t v3) {
  f[0] += bf_lo(v0); f[1] += bf_hi(v0); f[2] += bf_lo(v1); f[3] += bf_hi(v1); f[4] += bf_lo(v2); f[5] += bf_hi(v2); f[6] += bf_lo(v3); f[7] += bf_hi(v3);
}

struct cplx { float re, im; };
__device__ __forceinline__ cplx cmul(cplx a, cplx b) { return {fmaf(a.re, b.re, -a.im * b.im), fmaf(a.re, b.im, a.im * b.re)}; }
__device__ __forceinline__ cplx cexp_f(float ar, float ai) {
  float mag; asm("ex2.approx.f32 %0, %1;" : "=f"(mag) : "f"(ar * 1.4426950408889634f));
  const float k = rintf(ai * 0.15915494309189535f);
  float r = fmaf(ai, 0.15915494309189535f, -k);
  r = fmaf(ai, 6.4206383e-9f, r);
  r *= 6.283185307179586f;
  float sn, cs; asm("sin.approx.f32 %0, %1;" : "=f"(sn) : "f"(r)); asm("cos.approx.f32 %0, %1;" : "=f"(cs) : "f"(r));
  return {mag * cs, mag * sn};
}
__device__ __forceinline__ float bf2f(__nv_bfloat16 v) { return __bfloat162float(v); }

constexpr int KG_B = 32768, KG_TAB = 2688;

struct SsmParams { const __nv_bfloat16 *are, *aim, *bre, *bim, *cre, *cim, *logdt; };
struct ModeRaw { uint32_t are, aim, bre, bim, cre, cim; __nv_bfloat16 ldt; };
__device__ __forceinline__ ModeRaw load_mode(const SsmParams& p, int d, int t128) {
  const int o = d * 64 + t128;
  auto ld = [&](const __nv_bfloat16* b) { return __ldg((const uint32_t*)b + o); };
  return {ld(p.are), ld(p.aim), ld(p.bre), ld(p.bim), ld(p.cre), ld(p.cim), __ldg(p.logdt + d + (t128 >> 6))};
}

__device__ __forceinline__ void layer_norm16(int tid_);
__device__ __forceinline__ void kgen_powers(const ModeRaw& mr, int wg, int t128_, int row0, bool g_first) {
  const int t128 = opaque(t128_);
  const uint32_t scr = S_X + wg * 65536;
  const int warp = t128 >> 5, lane = t128 & 31;
  cplx cb[2], z1[2], zq[2];
  const float dt = bf_round(expf(bf2f(mr.ldt)));
  #pragma unroll
  for (int c = 0; c < 2; c++) {
    auto f = [&](uint32_t v) { return c ? bf_hi(v) : bf_lo(v); };
    const float ar = dt * f(mr.are), ai = dt * f(mr.aim);
    cb[c] = cmul({f(mr.cre), f(mr.cim)}, {dt * f(mr.bre), dt * f(mr.bim)});
    z1[c] = cexp_f(ar, ai); zq[c] = cexp_f(ar * 256.f, ai * 256.f);
  }
  KT(12);
  uint32_t ad[8];
  #pragma unroll
  for (int i = 0; i < 8; i++) ad[i] = scr + KG_B + ((warp & 1) * 2 + (lane >> 4)) * 6144 + (warp >> 1) * 3072 + (lane & 1) * 8 + ((((lane >> 1) & 7) ^ i) << 4);
  cplx z2[2];
  {
    auto put = [&](int b, const cplx* v) { sts64(ad[b & 7] + b * 128, pack_bf16(v[0].re, -v[0].im), pack_bf16(v[1].re, -v[1].im)); };
    cplx e[2], o[2], h[2], h0[2], h4[2];
    #pragma unroll
    for (int c = 0; c < 2; c++) { z2[c] = cmul(z1[c], z1[c]); e[c] = cb[c]; o[c] = cmul(cb[c], z1[c]); }
    #pragma unroll
    for (int i = 0; i < 4; i++) {
      put(2 * i, e); put(2 * i + 1, o);
      #pragma unroll
      for (int c = 0; c < 2; c++) {
        h[c] = cmul(e[c], zq[c]);
        if (i == 0) h0[c] = h[c];
        if (i == 2) h4[c] = h[c];
        if (i < 3) { e[c] = cmul(e[c], z2[c]); o[c] = cmul(o[c], z2[c]); }
      }
      put(8 + i, h);
    }
    #pragma unroll
    for (int i = 0; i < 7; i++) {
      #pragma unroll
      for (int c = 0; c < 2; c++) { h0[c] = cmul(h0[c], zq[c]); if (i < 2) h4[c] = cmul(h4[c], zq[c]); }
      put(i < 2 ? 12 + 2 * i : 14 + i, h0);
      if (i < 2) put(13 + 2 * i, h4);
    }
  }
  KT(13);
  if (row0 >= 0) layer_norm16(wg * 128 + t128);
  {
    #pragma unroll
    for (int i = 0; i < 8; i++) ad[i] += ((warp & 1) * 2 + (lane >> 4)) * 2048 + (warp >> 1) * 1024 - KG_B;
    cplx y[2][2], z16[2];
    #pragma unroll
    for (int c = 0; c < 2; c++) { const cplx z4 = cmul(z2[c], z2[c]); y[0][c] = {1.f, 0.f}; y[1][c] = cmul(z4, z4); z16[c] = cmul(y[1][c], y[1][c]); }
    #pragma unroll 1
    for (int jo = 0; jo < 4096; jo += 1024) {
      #pragma unroll
      for (int jj = 0; jj < 8; jj++) {
        sts64(ad[jj] + jo + jj * 128, pack_bf16(y[jj & 1][0].re, y[jj & 1][0].im), pack_bf16(y[jj & 1][1].re, y[jj & 1][1].im));
        #pragma unroll
        for (int c = 0; c < 2; c++) y[jj & 1][c] = cmul(y[jj & 1][c], z16[c]);
      }
    }
  }
  KT(14);
  fence_async_smem();
}
__device__ __forceinline__ void kgen_finish(int wg, int t128_, bool ln, bool g_first) {
  const int t128 = opaque(t128_);
  const uint32_t scr = S_X + wg * 65536;
  const int warp = t128 >> 5, lane = t128 & 31;
  bar_sync(2 + wg, 128);
  KT(15);
  float dd[24];
  {
    wg_fence();
    const uint64_t da = ((uint64_t)0x40000040u << 32) | opaque((scr >> 4) | 0x10000u), db = da + KG_B / 16;
    #pragma unroll
    for (int ks = 0; ks < 16; ks++) wgmma_ss_n48_t0(dd, da + (ks >> 2) * 512 + (ks & 3) * 2, db + (ks >> 2) * 384 + (ks & 3) * 2, ks != 0);
    wg_commit();
    wg_wait<0>();
  }
  KT(16);
  bar_sync(2 + wg, 128);
  {
    const int g = lane >> 2, q = lane & 3, hi = warp >> 1;
    const uint32_t tb = scr + hi * KG_TAB;
    #pragma unroll
    for (int rr = 0; rr < 2; rr++) {
      const int jj = (warp & 1) * 16 + g + rr * 8;
      float v[6];
      #pragma unroll
      for (int b = 0; b < 3; b++) { v[b * 2] = hi ? dd[12 + b * 4 + rr * 2] : dd[b * 4 + rr * 2]; v[b * 2 + 1] = hi ? dd[12 + b * 4 + rr * 2 + 1] : dd[b * 4 + rr * 2 + 1]; }
      sts64(tb + (8 * jj + 2 * q) * 4, __float_as_uint(v[0]), __float_as_uint(v[1]));
      sts64(tb + (q < 2 ? 256 + 4 * jj + 2 * q : 256 + 64 * q + 2 * jj) * 4, __float_as_uint(v[2]), __float_as_uint(v[3]));
      if (q < 2) { sts32(tb + (512 + 64 * q + jj) * 4, __float_as_uint(v[4])); sts32(tb + (544 + 64 * q + jj) * 4, __float_as_uint(v[5])); }
      else if (q == 2 && jj == 0) sts32(tb + 640 * 4, __float_as_uint(v[4]));
    }
  }
  KT(17);
  if (ln && wg == 0) mbar_wait(B_LN2, 0);
  bar_sync(2 + wg, 128);
  #pragma unroll
  for (int c = 0; c < 2; c++) {
    const uint32_t t0 = scr + c * KG_TAB, wp = s_w_of(wg * 2 + c) + 64 + t128 * 16;
    const int t = t128;
    float k0, k1, k2, k3, kp;
    if (warp < 2) {
      uint32_t a0, a1, a2, a3; lds128(t0 + 16 * t, a0, a1, a2, a3);
      k0 = __uint_as_float(a0); k1 = __uint_as_float(a1); k2 = __uint_as_float(a2); k3 = __uint_as_float(a3);
      kp = ldsf(t0 + 16 * t - (t ? 4 : 0)); if (t == 0) kp = 0.f;
    } else {
      uint32_t a0, a1; lds64(t0 + (128 + 2 * t) * 4, a0, a1);
      k0 = k1 = __uint_as_float(a0); k2 = __uint_as_float(a1); k3 = ldsf(t0 + (130 + 2 * t) * 4);
      kp = ldsf(t0 + (t == 64 ? 255 : 128 + 2 * t) * 4);
    }
    const float s0 = ldsf(t0 + (384 + t) * 4), s1 = ldsf(t0 + (385 + t) * 4);
    const int ph = t & 3, b3 = 512 + 2 * (t >> 2);
    const float a0 = ldsf(t0 + (b3 + (ph >> 1)) * 4), c0 = ldsf(t0 + (b3 + ((ph + 1) >> 1)) * 4);
    const float a1 = ldsf(t0 + (b3 + 64 + (ph >> 1)) * 4), c1 = ldsf(t0 + (b3 + 64 + ((ph + 1) >> 1)) * 4);
    sts128(wp, pack_bf16(k0, kp), pack_bf16(k1, k0), pack_bf16(k2, k1), pack_bf16(k3, k2));
    const float m = (t & 1) ? s1 : s0;
    sts128(wp + 2048, pack_bf16(s0, s0), pack_bf16(s0, s0), pack_bf16(m, s0), pack_bf16(s1, m));
    const float f0 = ph == 1 ? a0 : c0, f1 = ph == 1 ? a1 : c1;
    sts128(wp + 4096, pack_bf16(f0, a0), pack_bf16(c0, f0), pack_bf16(c0, c0), pack_bf16(c0, c0));
    sts128(wp + 6144, pack_bf16(f1, a1), pack_bf16(c1, f1), pack_bf16(c1, c1), pack_bf16(c1, c1));
    if (t < 4) sts128(wp - 64, 0, 0, 0, 0);
    if (!ln && t < 112) sts128(S_U - 3584 + c * 1792 + t * 16, 0, 0, 0, 0);
  }
}

template <int P> __device__ __forceinline__ void conv_step(float* acc, const uint32_t* fr, uint32_t db) {
  uint32_t lo; asm volatile("sub.u32 %0, %1, %2;" : "=r"(lo) : "r"(db), "n"(32 * P - 256 * 3));
  uint64_t d = ((uint64_t)0x40000040u << 32) | lo;
  #pragma unroll
  for (int sg = 3; sg >= P / 8; sg--) wgmma_rs_n32_t0(acc + 16 * sg, fr[0], fr[1], fr[2], fr[3], d - 256 * (3 - sg), P != 0);
}
template <int I, int I1> struct ConvPairs {
  static __device__ __forceinline__ void run(float* acc, const uint32_t* fr, uint32_t db) {
    conv_step<I>(acc, fr + I * 4, db); conv_step<31 - I>(acc, fr + (31 - I) * 4, db);
    ConvPairs<I + 1, I1>::run(acc, fr, db);
  }
};
template <int I1> struct ConvPairs<I1, I1> { static __device__ __forceinline__ void run(float*, const uint32_t*, uint32_t) {} };

__device__ __forceinline__ void conv_reduce(uint32_t s_r, int t128, __nv_bfloat16* yrow) {
  #pragma unroll
  for (int h = 0; h < 2; h++) {
    const int cc = t128 + h * 128;
    uint32_t v[4][4];
    #pragma unroll
    for (int b = 0; b < 4; b++) {
      lds128(s_r + b * 4096 + cc * 16, v[b][0], v[b][1], v[b][2], v[b][3]);
      if (h == 0 && b > (cc >> 1)) { v[b][0] = v[b][1] = v[b][2] = v[b][3] = 0; }
    }
    uint32_t o[4];
    #pragma unroll
    for (int e = 0; e < 4; e++) { const uint32_t p = add_bf16x2(v[0][e], v[1][e]), q = add_bf16x2(v[2][e], v[3][e]); o[e] = add_bf16x2(p, q); }
    *(uint4*)(yrow + cc * 8) = make_uint4(o[0], o[1], o[2], o[3]);
  }
}
__device__ __forceinline__ void conv_one(int wg, int c, int t128_, int uphase, __nv_bfloat16* y0) {
  const int t128 = opaque(t128_), ch = wg * 2 + c;
  const uint32_t s_w = s_w_of(ch), s_r = S_X + wg * 65536 + 49152;
  const int warp = t128 >> 5, lane = t128 & 31;
  float acc[64];
  uint32_t fr[128];
  const uint32_t wa = s_w + 64 + (warp * 16 + (lane >> 2) - 2 * (lane & 3)) * 4;
  const uint32_t zero = lds32(s_w);
  auto ld = [&](int p) { fr[p * 4] = lds32(wa + p * 256); fr[p * 4 + 1] = lds32(wa + p * 256 + 32); fr[p * 4 + 2] = lds32(wa + p * 256 - 32);
                         asm volatile("xor.b32 %0, %1, %2;" : "=r"(fr[p * 4 + 3]) : "r"(fr[p * 4]), "r"(zero)); };
  const uint32_t db = ((S_U >> 4) | 0x10000u) + ch * 2;
  #pragma unroll
  for (int p = 0; p < 32; p++) ld(p);
  CT(0);
  if (c == 0) mbar_wait(B_U, uphase);
  mbar_wait(B_PP + 8 * wg, wg ? c ^ 1 : c);
  CT(1);
  wg_fence();
  ConvPairs<0, 16>::run(acc, fr, db);
  wg_commit();
  if (lane == 0) mbar_arrive(B_PP + 8 - 8 * wg);
  if (c == 1) conv_reduce(s_r, t128, y0);
  CT(2);
  wg_wait<0>();
  CT(3);
  if (c == 1 && lane == 0) mbar_arrive(B_CDONE);
  if (c == 1) bar_sync(2 + wg, 128);
  const int col = 8 * (lane >> 4) + (lane & 7) + warp;
  const uint32_t ra = s_r + warp * 4096 + (col * 16 + ((lane >> 3) & 1) * 8) * 2;
  #pragma unroll
  for (int v = 0; v < 8; v++)
    asm volatile("stmatrix.sync.aligned.m8n8.x4.trans.shared.b16 [%0], {%1,%2,%3,%4};" :: "r"((v == 7 && col >= 16) ? S_DUMMY : ra + v * 512),
                 "r"(pack_bf16(acc[v * 8], acc[v * 8 + 1])), "r"(pack_bf16(acc[v * 8 + 2], acc[v * 8 + 3])), "r"(pack_bf16(acc[v * 8 + 4], acc[v * 8 + 5])), "r"(pack_bf16(acc[v * 8 + 6], acc[v * 8 + 7])) : "memory");
  bar_sync(2 + wg, 128);
  CT(4);
}

__device__ __forceinline__ void layer_norm16(int tid_) {
  const int tid = opaque(tid_), row = tid >> 4, l16 = tid & 15;
  const bool g_first = true; (void)g_first;
  const uint32_t ra = S_LN + (l16 >> 3) * 2048 + row * 128 + (((l16 & 7) ^ (row & 7)) << 4);
  uint32_t v[20];
  KT(20);
  mbar_wait(B_RAW, 0);
  KT(21);
  #pragma unroll
  for (int i = 0; i < 4; i++) lds128(ra + i * 4096, v[i * 4], v[i * 4 + 1], v[i * 4 + 2], v[i * 4 + 3]);
  v[16] = v[17] = v[18] = v[19] = 0;
  if (l16 < 8) lds128(ra + 16384, v[16], v[17], v[18], v[19]);
  float s0 = 0.f, s1 = 0.f, q0 = 0.f, q1 = 0.f;
  #pragma unroll
  for (int e = 0; e < 20; e++) { const float lo = bf_lo(v[e]), hi = bf_hi(v[e]); s0 += lo; s1 += hi; q0 = fmaf(lo, lo, q0); q1 = fmaf(hi, hi, q1); }
  float s = s0 + s1, ss = q0 + q1;
  #pragma unroll
  for (int o = 8; o; o >>= 1) { s += __shfl_xor_sync(0xffffffffu, s, o); ss += __shfl_xor_sync(0xffffffffu, ss, o); }
  const float mean = s * (1.f / D_), var = fmaxf(fmaf(-mean, mean, ss * (1.f / D_)), 0.f);
  const uint32_t mb = pack_bf16(mean, mean);
  const float rs = 1.0f / bf_round(sqrtf(bf_round(bf_round(var) + 1e-5f)));
  const uint32_t rh = pack_bf16(rs, rs), rl = pack_bf16(rs - bf_lo(rh), rs - bf_lo(rh));
  KT(22);
  #pragma unroll
  for (int e = 0; e < 20; e++) { const uint32_t dd = sub_bf16x2(v[e], mb); asm("fma.rn.bf16x2 %0, %1, %2, %3;" : "=r"(v[e]) : "r"(dd), "r"(rh), "r"(mul_bf16x2(dd, rl))); }
  #pragma unroll
  for (int i = 0; i < 5; i++) if (i < 4 || l16 < 8) sts128(ra + i * 4096, v[i * 4], v[i * 4 + 1], v[i * 4 + 2], v[i * 4 + 3]);
  KT(23);
  bar_sync(4, 256);
  {
    const int warp = tid >> 5, lane = tid & 31, r = lane & 7, e = lane >> 3, tok = (r >> 1) * 4 + (r & 1) + (e & 1) * 2;
    const uint32_t la = S_LN + (warp >> 2) * 2048 + tok * 128 + ((((warp & 3) * 2 + (e >> 1)) ^ (tok & 7)) << 4), ta = S_LN + 18432 + warp * 512 + lane * 8;
    #pragma unroll
    for (int i = 0; i < 5; i++) if (i < 4 || warp < 4) ldsm_x4t(la + i * 4096, v[i * 4], v[i * 4 + 1], v[i * 4 + 2], v[i * 4 + 3]);
    #pragma unroll
    for (int i = 0; i < 5; i++) if (i < 4 || warp < 4) { sts64(ta + i * 4096, v[i * 4], v[i * 4 + 1]); sts64(ta + i * 4096 + 256, v[i * 4 + 2], v[i * 4 + 3]); }
  }
  fence_async_smem();
  __syncwarp();
  if ((tid & 31) == 0) mbar_arrive(B_LN);
  KT(24);
}

__device__ __forceinline__ void ssm_phase(const SsmParams& p, ModeRaw mr, int wg, int d0, int npair, int row0, int t128) {
  int d = d0 + wg * 2;
  #pragma unroll 1
  for (int it = 0; it < npair; it++, d += 4) {
    kgen_powers(mr, wg, t128, row0, it == 0);
    kgen_finish(wg, t128, row0 >= 0, it == 0);
    fence_async_smem();
    __syncwarp();
    if ((t128 & 31) == 0) mbar_arrive(B_KDONE + 8 * wg);
    bar_sync(2 + wg, 128);
    if (it == 0) { TSTAMP(10); GSTAMP(5); }
    #pragma unroll 1
    for (int c = 0; c < 2; c++) conv_one(wg, c, t128, it & 1, g_yt + d * L_);
    conv_reduce(S_X + wg * 65536 + 49152, opaque(t128), g_yt + (d + 1) * L_);
    fence_async_smem();
    __syncwarp();
    if ((t128 & 31) == 0) mbar_arrive(B_RDONE + 8 * wg);
    if (it + 1 < npair) { mr = load_mode(p, d + 4, t128); bar_sync(4, 256); }
  }
  if ((t128 & 31) == 0) mbar_arrive(B_YDONE);
}

#define RELPOS 6
#define PACE 600
struct Ring { bool ready; int ts; unsigned int wt; };
__device__ __forceinline__ void arrive_one(uint32_t bar) {
  asm volatile("{\n.reg .pred p;\nelect.sync _|p, 0xffffffff;\n@p mbarrier.arrive.shared::cta.b64 _, [%0];\n}\n" :: "r"(bar) : "memory");
}

template <int PH, int KB0 = 0, int KB1 = 6, bool FIRST = false, bool LAST = false, class Pre, class Slice>
__device__ __forceinline__ void run_pass(float* acc, uint32_t* a, Ring& r, Pre pre, Slice slice) {
  #pragma unroll
  for (int kb = KB0; kb < KB1; kb++) {
    pre(kb);
    if (!r.ready) mbar_wait(B_FULL + 8 * kb, PH);
    if (r.ts >= 0) TSTAMP(r.ts + kb * 2);
    wg_fence();
    const uint64_t d0 = ((uint64_t)0x40000040u << 32) | ((S_RING + kb * STG_BYTES) >> 4) | (512u << 16);
    #pragma unroll
    for (int kk = 0; kk < 6; kk++) {
      wgmma_rs_n64_t1(acc, a[(kb * 6 + kk) * 4 + 0], a[(kb * 6 + kk) * 4 + 1], a[(kb * 6 + kk) * 4 + 2], a[(kb * 6 + kk) * 4 + 3], d0 + kk * 128, (kb | kk) != 0);
      if (kk == RELPOS && (kb > 0 || !FIRST)) { wg_wait<0>(); arrive_one(B_EMPTY + 8 * ((kb + 5) % 6)); }
      if (kk == SLPOS) slice(kb);
    }
    wg_commit();
    if (!LAST) r.ready = mbar_try_wait(B_FULL + 8 * ((kb + 1) % 6), kb == 5 ? PH ^ 1 : PH);
    if (SLPOS >= 6) slice(kb);
    if (r.ts >= 0) TSTAMP(r.ts + kb * 2 + 1);
    if (RELPOS >= 6 && (kb > 0 || !FIRST)) {
      wg_wait<1>();
      arrive_one(B_EMPTY + 8 * ((kb + 5) % 6));
    }
  }
}

struct CtaId { int m, j; };
__device__ __forceinline__ CtaId map_cta(int bx) {
  if (MAPMODE == 0) return {bx & 15, bx >> 4};
  if (MAPMODE == 2) return {((bx >> 6) << 3) + ((bx >> 1) & 7), (((bx >> 4) & 3) << 1) + (bx & 1)};
  if (MAPMODE == 3) return {((bx >> 6) << 3) + (bx & 7), (((bx >> 4) & 3) << 1) + ((bx >> 3) & 1)};
  if (MAPMODE == 4) return {((bx >> 5) << 2) + (bx & 3), (((bx >> 4) & 1) << 2) + ((bx >> 2) & 3)};
  return {((bx >> 5) << 2) + ((bx >> 2) & 3), (((bx >> 4) & 1) << 2) + (bx & 3)};
}
__device__ __forceinline__ CtaId cta_id() {
  int bx; asm volatile("mov.u32 %0, %%ctaid.x;" : "=r"(bx));
  bx = __shfl_sync(0xffffffffu, bx, 0);
  return map_cta(bx);
}
__device__ __forceinline__ CtaId cta_id_lane() {
  int bx; asm volatile("mov.u32 %0, %%ctaid.x;" : "=r"(bx));
  return map_cta(bx);
}
struct Maps { CUtensorMap xraw3, x2, xt, xt64, xt8, yt, w1, w3, w2, x8, yt8; };

__global__ void __launch_bounds__(NTHR, 1) k_main(const __grid_constant__ Maps tm, const SsmParams sp, const __nv_bfloat16* __restrict__ dskip,
                                                   __nv_bfloat16* __restrict__ out) {
  extern __shared__ unsigned char smem_raw[];
  const int tid = threadIdx.x, wg = __shfl_sync(0xffffffffu, tid >> 7, 0);
  const int bx = blockIdx.x;
  const bool ffn = bx < NFFN;
  const int m = map_cta(bx).m, j = map_cta(bx).j;
  const int d0 = ffn ? bx * 4 : 512 + (bx - NFFN) * 16, npair = ffn ? 1 : 4;
  if (smem_u32(smem_raw) != S_X) return;
  if (tid == 0) TSTAMP(0);
  GSTAMP(0);
  if (wg == 2) {
    asm volatile("setmaxnreg.dec.sync.aligned.u32 24;");
    if (tid == 256) {
      mbar_init(B_RAW, 1);
      asm volatile("fence.mbarrier_init.release.cluster;" ::: "memory");
      if (ffn) { mbar_expect_tx(B_RAW, 18432); tma3d(S_LN, &tm.xraw3, 0, m * 128 + j * 16, 0, B_RAW); }
    } else if (tid >= 288 && tid < 336) {
      const int bi = tid - 288;
      const uint64_t tab = bi < 16 ? 0x88888800111111ull : (bi < 32 ? 0x8440180028011111ull : 0x111188814481440ull);
      const uint32_t c = (uint32_t)(tab >> (4 * (bi & 15))) & 15u;
      if (c) mbar_init(S_BAR + 8 * bi, (bi == 27 && ffn) ? 2 : c);
      asm volatile("fence.mbarrier_init.release.cluster;" ::: "memory");
    }
    bar_sync(0, NTHR);
    const int pw = (tid >> 5) & 3, lane = tid & 31;
    if (pw == 0) {
      if (lane == 0) {
        auto wload0 = [&](int kb0) {
          #pragma unroll 1
          for (int kb = kb0; kb < kb0 + 3; kb++) { mbar_expect_tx(B_FULL + 8 * kb, STG_BYTES); tma2d(S_RING + kb * STG_BYTES, &tm.w1, j * 576, kb * 96, B_FULL + 8 * kb); }
        };
        const unsigned int epoch = cur_epoch();
        if (ffn) {
          mbar_wait(B_RAW, 0);
          wload0(0);
        }
        if (ffn) mbar_wait(B_LN2, 0); else __nanosleep(2500);
        #pragma unroll 1
        for (int it = 0; it < 8192; it++) { unsigned int v; asm volatile("ld.acquire.gpu.global.u32 %0, [%1];" : "=r"(v) : "l"(&g_cnt_all) : "memory"); if (v == epoch * NFFN) break; }
        fence_async();
        TSTAMP1(2, 1);
        #pragma unroll 1
        for (int it = 0; it < npair; it++) {
          if (it > 0) mbar_wait(B_CDONE, (it - 1) & 1);
          mbar_expect_tx(B_U, 16384);
          tma2d(S_U, &tm.xt, (d0 + it * 4) * 16, 0, B_U);
        }
        if (ffn) {
          #pragma unroll 1
          for (int w = 0; w < 2; w++) {
            mbar_wait(B_KDONE + 8 * w, 0);
            mbar_expect_tx(B_X + 8 * w, 3 * 16384);
            #pragma unroll 1
            for (int q = 0; q < 3; q++) tma3d(S_X + w * 65536 + q * 16384, &tm.xt64, 0, (w * 3 + q) * 16, m * 8, B_X + 8 * w);
          }
          mbar_wait(B_CDONE, 0);
          wload0(3);
          #pragma unroll 1
          for (int w = 0; w < 3; w++) {
            if (w > 0) mbar_wait(B_RDONE - 8 + 8 * w, 0);
            const uint32_t bar = B_X + (w ? 8 + 8 * w : 32);
            mbar_expect_tx(bar, 16384); tma3d(S_X + (w ? 4 * w - 1 : 8) * 16384, &tm.xt64, 0, w ? 80 + 16 * w : 128, m * 8, bar);
          }
          auto wpass = [&](const CUtensorMap* t, int c0, int c1, uint32_t par) {
            #pragma unroll
            for (int kb = 0; kb < 6; kb++) {
              mbar_spin(B_EMPTY + 8 * kb, par);
              mbar_expect_tx(B_FULL + 8 * kb, STG_BYTES);
              tma2d(S_RING + kb * STG_BYTES, t, c0, c1 + kb * 96, B_FULL + 8 * kb);
            }
          };
          const CUtensorMap* t = &tm.w3; int c0 = j * 576, c1 = 0;
          #pragma unroll 1
          for (int p = 1; p < 27; p++) {
            wpass(t, c0, c1, (p - 1) & 1);
            if (p < 17) { t = (p & 1) ? &tm.w1 : &tm.w3; c0 += (p & 1) * 64; }
            else { t = &tm.w2; c1 = j * 576; c0 = p == 17 ? 512 : ((j + p - 17) & 7) * 64; }
          }
        }
      }
      __syncwarp();
    } else {
      const int hw = pw - 1;
      if (tid == 352) { sts32(S_DSK + 196, atomicAdd(&g_ticket, 1) / NCTA + 1); mbar_arrive(B_EP); }
      if (tid == 320) { prefetch_tmap(&tm.xt); prefetch_tmap(&tm.w1); prefetch_tmap(&tm.xt64); prefetch_tmap(&tm.w3); }
      __syncwarp();
      if (hw == 0) {
        const unsigned int epoch = cur_epoch();
        if (ffn) { const uint32_t* dp = (const uint32_t*)dskip; sts32(S_DSK + lane * 4, __ldg(dp + j * 32 + (lane & 24) + ((lane >> 1) & 3) + (lane & 1) * 4)); if (lane < 4) sts32(S_DSK + 128 + lane * 4, __ldg(dp + 256 + j * 4 + lane)); }
        if (ffn && lane == 0) {
          mbar_wait(B_LN, 0);
          TSTAMP1(2, 2);
          asm volatile("cp.async.bulk.global.shared::cta.bulk_group [%0], [%1], %2;" :: "l"(g_xt + (m * 128 + j * 16) * D_), "r"(S_LN + 18432), "r"(18432) : "memory");
          asm volatile("cp.async.bulk.commit_group;" ::: "memory");
          asm volatile("cp.async.bulk.wait_group 0;" ::: "memory");
          TSTAMP1(2, 14);
          fence_async();
          red_add(&g_cnt_all);
          mbar_arrive(B_LN2); TSTAMP1(2, 3);
        }
        __syncwarp();
        if (ffn) {
          #pragma unroll
          for (int i = 0; i < 7; i++) sts128(S_U - 3584 + i * 512 + lane * 16, 0, 0, 0, 0);
          fence_async_smem();
          __syncwarp();
          if (lane == 0) mbar_arrive(B_U);
        }
        mbar_wait(B_CDONE, 0);
        if (ffn) {
          uint4* za = g_acc + (m * 9 + j) * 1024 + lane;
          #pragma unroll 1
          for (int i = 0; i < 32; i++) za[i * 32] = make_uint4(0, 0, 0, 0);
          za = g_acc + (m * 9 + 8) * 1024 + j * 128 + lane;
          #pragma unroll 1
          for (int i = 0; i < 4; i++) za[i * 32] = make_uint4(0, 0, 0, 0);
        }
        __syncwarp();
        if (lane == 0) {
          mbar_wait(B_YDONE, 0);
          fence_gpu(); red_add(ffn ? &g_cnt_y : &g_cnt_ys);
          if (ffn) {
            prefetch_tmap(&tm.x2); prefetch_tmap(&tm.yt); prefetch_tmap(&tm.x8); prefetch_tmap(&tm.xt8); prefetch_tmap(&tm.yt8); prefetch_tmap(&tm.w2);
            flag_wait(&g_cnt_y, epoch * NFFN, 500); fence_async();
            mbar_arrive(B_GO);
            mbar_wait(B_PFREE, 0);
            mbar_expect_tx(B_H, 49152);
            __nanosleep(PACE); tma2d(S_X + 2 * 16384, &tm.x2, j * 64, m * 128, B_H); __nanosleep(PACE); tma3d(S_X + 3 * 16384, &tm.xt64, 0, j * 16, m * 8, B_H); __nanosleep(PACE);
            tma2d(S_X + 4 * 16384, &tm.yt, m * 128, j * 64, B_H); tma2d(S_X + 4 * 16384 + 8192, &tm.yt, m * 128 + 64, j * 64, B_H);
            TSTAMP1(2, 4);
            #pragma unroll 1
            for (int k = 0; k < 3; k++) {
              mbar_wait(B_PUB + 8 * k, 0);
              fence_gpu();
              red_add(&g_cnt_acc[(m * 9 + (k ? (j + 2 * k) & 7 : 8)) * 8]);
              if (k < 2) red_add(&g_cnt_acc[(m * 9 + ((j + 2 * k + 1) & 7)) * 8]);
              TSTAMP1(2, 8 + k);
            }
          }
        }
        __syncwarp();
      }
      if (ffn) {
        if (hw == 1 && lane == 0) {
          const CtaId id = cta_id_lane();
          mbar_wait(B_RAW, 0);
          #pragma unroll 1
          for (int p = 0; p < 27; p++) {
            if (p > PFLA) mbar_wait(B_FULL, (p - PFLA - 1) & 1);
            const int kb = (id.m - p * 6) & 15;
            if (kb < 6) {
              const CUtensorMap* t = p < 18 ? ((p & 1) ? &tm.w3 : &tm.w1) : &tm.w2;
              const int c0 = p < 18 ? id.j * 576 + (p >> 1) * 64 : (p == 18 ? 8 : ((id.j + p - 18) & 7)) * 64, c1 = (p < 18 ? 0 : id.j * 576) + kb * 96;
              asm volatile("cp.async.bulk.prefetch.tensor.2d.L2.global [%0, {%1, %2}];" :: "l"(t), "r"(c0), "r"(c1) : "memory");
            }
          }
        }
        __syncwarp();
        if (hw > 0) {
          mbar_wait(B_H, 0);
          {
            const uint32_t r7 = lane & 7, dq = (lane >> 4) * 2 + (r7 >> 2);
            const uint32_t na = S_X + 3 * 16384 + dq * 128 + ((((lane & 3) * 2 + ((lane >> 3) & 1)) ^ dq) << 4);
            const uint32_t ya = S_X + 4 * 16384 + ((lane >> 4) * 8 + r7) * 128 + ((((lane >> 3) & 1) ^ r7) << 4);
            const uint32_t xa = S_X + 2 * 16384 + (lane & 15) * 128 + (((lane >> 4) ^ r7) << 4);
            #pragma unroll 1
            for (int k = __shfl_sync(0xffffffffu, hw, 0) - 1; k < 32; k += 2) {
              const uint32_t hf = (k >> 4) * 8192, i = (k >> 2) & 3, wp = k & 3;
              uint32_t x[4], n[4], y[4], k0, k1;
              ldsm_x4t((na ^ ((i & 1) * 64)) + hf + wp * 2048 + i * 512, n[0], n[1], n[2], n[3]);
              ldsm_x4t((ya ^ (wp * 32)) + hf + i * 2048, y[0], y[1], y[2], y[3]);
              ldsm_x4((xa ^ (i * 32)) + hf + wp * 2048, x[0], x[1], x[2], x[3]);
              lds64(S_DSK + i * 32 + (lane & 3) * 8, k0, k1);
              sts128(S_X + 7 * 16384 + k * 512 + lane * 16, add_bf16x2(x[0], add_bf16x2(y[0], mul_bf16x2(n[0], k0))), add_bf16x2(x[1], add_bf16x2(y[1], mul_bf16x2(n[1], k0))),
                     add_bf16x2(x[2], add_bf16x2(y[2], mul_bf16x2(n[2], k1))), add_bf16x2(x[3], add_bf16x2(y[3], mul_bf16x2(n[3], k1))));
            }
          }
          __syncwarp();
          if (lane == 0) {
            mbar_arrive(B_BASE);
            TSTAMP1(2, 5 + hw);
            const CtaId id = cta_id_lane();
            const unsigned int epoch = cur_epoch();
            if (hw == 1) {
              flag_wait(&g_cnt_acc[(id.m * 9 + id.j) * 8], epoch * 4, 100); fence_async();
              mbar_expect_tx(B_R, 16384); bulk_g2s(S_X + 6 * 16384, g_acc + (id.m * 9 + id.j) * 1024, 16384, B_R);
              TSTAMP1(2, 12);
            } else {
              flag_wait(&g_cnt_ys, epoch * (NCTA - NFFN), 300);
              flag_wait(&g_cnt_acc[(id.m * 9 + 8) * 8], epoch * 8, 300); fence_async();
              mbar_expect_tx(B_H8, 8192);
              tma2d(S_X + 8 * 16384, &tm.x8, 512 + id.j * 8, id.m * 128, B_H8); tma3d(S_X + 8 * 16384 + 2048, &tm.xt8, 0, 128 + id.j * 2, id.m * 8, B_H8);
              tma2d(S_X + 8 * 16384 + 4096, &tm.yt8, id.m * 128, 512 + id.j * 8, B_H8); tma2d(S_X + 8 * 16384 + 5120, &tm.yt8, id.m * 128 + 64, 512 + id.j * 8, B_H8);
              bulk_g2s(S_X + 8 * 16384 + 6144, g_acc + (id.m * 9 + 8) * 1024 + id.j * 128, 2048, B_H8);
            }
          }
          __syncwarp();
          if (hw == 2) {
            mbar_wait(B_H8, 0);
            const CtaId id = cta_id();
            const uint32_t h2 = (lane >> 2) & 1, hb = (lane >> 3) & 1;
            const uint32_t ta = (lane & 16) ? S_X + 8 * 16384 + 4096 + (lane & 7) * 128 + ((hb ^ (lane & 7)) << 4) : S_X + 8 * 16384 + 2048 + h2 * 128 + ((((lane & 3) * 2 + hb) ^ h2) << 4);
            const uint32_t k0 = lds32(S_DSK + 128 + (lane & 3) * 4);
            __nv_bfloat16* op = out + (id.m * 128 * D_ + 512 + id.j * 8) + (lane >> 2) * D_ + (lane & 3) * 2;
            #pragma unroll 1
            for (int k = 0; k < 8; k++, op += 16 * D_) {
              uint32_t x0, x1, n0, n1, y0, y1, v0, v1;
              asm volatile("ldmatrix.sync.aligned.m8n8.x2.shared.b16 {%0,%1}, [%2];" : "=r"(x0), "=r"(x1) : "r"(S_X + 8 * 16384 + k * 256 + (lane & 15) * 16) : "memory");
              ldsm_x4t((ta ^ ((k & 3) * 32)) + ((lane & 16) ? (k >> 2) * 1024 : k * 256), n0, n1, y0, y1);
              lds64(S_X + 8 * 16384 + 6144 + k * 256 + lane * 8, v0, v1);
              *(uint32_t*)op = add_bf16x2(add_bf16x2(x0, add_bf16x2(y0, mul_bf16x2(n0, k0))), v0);
              *(uint32_t*)(op + 8 * D_) = add_bf16x2(add_bf16x2(x1, add_bf16x2(y1, mul_bf16x2(n1, k0))), v1);
            }
            if (lane == 0) TSTAMP1(2, 13);
          }
        }
      }
    }
  } else {
    asm volatile("setmaxnreg.inc.sync.aligned.u32 240;");
    const ModeRaw mr0 = load_mode(sp, d0 + wg * 2, tid & 127);
    bar_sync(0, NTHR);
    const int t128 = tid & 127, warp = t128 >> 5, lane = tid & 31;
    { const bool g_first = true; (void)g_first; KT(19); }
    ssm_phase(sp, mr0, wg, d0, npair, ffn ? m * 128 + j * 16 : -1, t128);
    TSTAMP(9); GSTAMP(1);
    if (ffn) {
    uint32_t a[144];
    float accG[32], accU[32];
    Ring r{false, -1, 0};
    const uint32_t park = S_X + wg * 8192 + t128 * 16;
    auto nop = [](int) {};
    auto silu_slice = [&](int kb, int t) {
      if (kb >= 1 && kb <= 4) {
        const int i0 = (kb - 1) * 8;
        sts128(park + t * 16384 + (kb - 1) * 2048, pack_bf16(silu_f(accG[i0]), silu_f(accG[i0 + 1])), pack_bf16(silu_f(accG[i0 + 2]), silu_f(accG[i0 + 3])),
               pack_bf16(accG[i0 + 4], accG[i0 + 5]), pack_bf16(accG[i0 + 6], accG[i0 + 7]));
      }
    };
    auto mul_unit = [&](int i, int t, uint32_t& h0, uint32_t& h1, uint32_t& h2, uint32_t& h3) {
      uint32_t s0, s1, g2, g3; const int i0 = i * 8;
      lds128(park + t * 16384 + i * 2048, s0, s1, g2, g3);
      h0 = mul_bf16x2(s0, pack_bf16(accU[i0], accU[i0 + 1])); h1 = mul_bf16x2(s1, pack_bf16(accU[i0 + 2], accU[i0 + 3]));
      h2 = mul_bf16x2(pack_bf16(silu_f(bf_lo(g2)), silu_f(bf_hi(g2))), pack_bf16(accU[i0 + 4], accU[i0 + 5]));
      h3 = mul_bf16x2(pack_bf16(silu_f(bf_lo(g3)), silu_f(bf_hi(g3))), pack_bf16(accU[i0 + 6], accU[i0 + 7]));
    };
    {
      const uint32_t xrow = (lane >> 4) * 2 + ((lane >> 2) & 1);
      const uint32_t rbase = S_X + wg * 8192 + warp * 2048 + xrow * 128 + ((((lane & 3) * 2 + ((lane >> 3) & 1)) ^ xrow) << 4);
      auto ldx = [&](int kb) {
          if (kb == 0) mbar_wait(B_X, 0);
          if (kb == 2) mbar_wait(B_X + 8, 0);
          if (kb == 4) { mbar_wait(B_X + 16, 0); mbar_wait(B_X + 24, 0); }
          if (kb == 5) mbar_wait(B_X + 32, 0);
          #pragma unroll
          for (int kk = 0; kk < 6; kk++) {
            const int ks = kb * 6 + kk;
            ldsm_x4t((rbase ^ ((ks & 1) * 64)) + xslot(ks >> 2) * 16384 + (ks & 3) * 512, a[ks * 4 + 0], a[ks * 4 + 1], a[ks * 4 + 2], a[ks * 4 + 3]);
          }
          if (kb == 0) TSTAMP(1);
        };
      run_pass<0, 0, 5, true>(accG, a, r, ldx, nop);
      ldx(5);
    }
    bar_sync(2 + wg, 128);
    auto reload = [&](int grp, int on) {
      #pragma unroll
      for (int i = 0; i < 6; i++) {
        const int q = grp * 6 + i;
        if (q < 32) asm volatile("{\n.reg .pred p;\nsetp.ne.b32 p, %5, 0;\n@p ld.shared.v4.b32 {%0,%1,%2,%3}, [%4];\n}\n"
                                 : "+r"(a[q * 4]), "+r"(a[q * 4 + 1]), "+r"(a[q * 4 + 2]), "+r"(a[q * 4 + 3]) : "r"(park + (q >> 2) * 16384 + (q & 3) * 2048), "r"(on) : "memory");
      }
    };
    #pragma unroll 1
    for (int t = 0; t < 9; t++) {
      run_pass<0, 5, 6>(accG, a, r, nop, nop);
      run_pass<1>(accU, a, r, nop, [&](int kb) { silu_slice(kb, t); if (kb >= 2) reload(kb - 2, t == 8); });
      run_pass<0, 0, 5>(accG, a, r, nop, [&](int kb) {
        if (kb <= 1) reload(4 + kb, t == 8);
        if (kb >= 1) {
          uint32_t h0, h1, h2, h3; mul_unit(kb - 1, t, h0, h1, h2, h3);
          sts128(park + t * 16384 + (kb - 1) * 2048, h0, h1, h2, h3);
          asm volatile("{\n.reg .pred p;\nsetp.ne.b32 p, %8, 0;\n@p mov.b32 %0, %4;\n@p mov.b32 %1, %5;\n@p mov.b32 %2, %6;\n@p mov.b32 %3, %7;\n}\n"
                       : "+r"(a[124 + kb * 4]), "+r"(a[125 + kb * 4]), "+r"(a[126 + kb * 4]), "+r"(a[127 + kb * 4]) : "r"(h0), "r"(h1), "r"(h2), "r"(h3), "r"((int)(t == 8)));
        } });
      r.ts = -1;
      if (t == 0) { TSTAMP(2); GSTAMP(2); }
      if (t == 3) { TSTAMP(11); GSTAMP(6); }
      if (t == 7) { TSTAMP(3); GSTAMP(3); }
    }
    TSTAMP(4);
    fence_async_smem(); __syncwarp(); arrive_one(B_PFREE);
    const uint32_t tag = opaque(cur_epoch() & 1);
    const CtaId id2 = cta_id(); const int m = id2.m, j = id2.j;
    const uint32_t pk = park - S_X;
    auto store_vec = [&](const float* acc, int t, int i, bool may0) {
      uint32_t w0 = pack_bf16(acc[i * 8], acc[i * 8 + 1]), w1 = pack_bf16(acc[i * 8 + 2], acc[i * 8 + 3]), w2 = pack_bf16(acc[i * 8 + 4], acc[i * 8 + 5]), w3 = pack_bf16(acc[i * 8 + 6], acc[i * 8 + 7]);
      if (may0 && __builtin_expect(t == 0, 0)) {
        if (i == 0) mbar_wait(B_GO, 0);
        const uint32_t pq = opaque(pk);
        char* dst = (char*)g_acc + (size_t)(m * 9 + 8) * 16384 + i * 4096 + (((pq >> 1) & 1023) | ((pq >> 3) & 1024));
        asm volatile("red.relaxed.gpu.global.add.noftz.v2.bf16x2 [%0], {%1,%2};" :: "l"(dst), "r"(w0), "r"(w1) : "memory");
        asm volatile("red.relaxed.gpu.global.add.noftz.v2.bf16x2 [%0], {%1,%2};" :: "l"(dst + 2048), "r"(w2), "r"(w3) : "memory");
      } else {
        const int blk = (j + t) & 7;
        const char* base = t >= 5 ? (const char*)g_part + (size_t)((m * 8 + blk) * 3 + t - 5) * 16384 : (const char*)g_acc + (size_t)(m * 9 + blk) * 16384;
        asm volatile("{\n.reg .pred p;\n.reg .b32 a, b, c, d;\nsetp.ge.s32 p, %6, 5;\n"
                     "lop3.b32 a, %1, -2, %5, 0xEA;\nlop3.b32 b, %2, -2, %5, 0xEA;\nlop3.b32 c, %3, -2, %5, 0xEA;\nlop3.b32 d, %4, -2, %5, 0xEA;\n"
                     "@p st.relaxed.gpu.global.v4.b32 [%0], {a,b,c,d};\n@!p red.relaxed.gpu.global.add.noftz.v4.bf16x2 [%0], {%1,%2,%3,%4};\n}\n"
                     :: "l"(base + i * 2048 + pk), "r"(w0), "r"(w1), "r"(w2), "r"(w3), "r"(tag), "r"(t) : "memory");
        if (i == 3) { __syncwarp(); asm volatile("{\n.reg .pred p, q;\nelect.sync _|p, 0xffffffff;\nsetp.ne.and.b32 q, %1, 0, p;\n@q mbarrier.arrive.shared::cta.b64 _, [%0];\n}\n" :: "r"(B_PUB + 8 * (t >> 1)), "r"((int)(t < 5 && t != 2)) : "memory"); }
      }
    };
    auto own_part = [&](int s) { return (const char*)g_part + (size_t)((m * 8 + j) * 3 + s - 5) * 16384 + pk; };
    auto fetch = [&](int s) {
      const char* src = own_part(s);
      #pragma unroll
      for (int i = 0; i < 4; i++) cp_async16(park + (s == 7 ? 5 : (s & 1)) * 16384 + i * 2048, src + i * 2048);
      cp_commit();
    };
    uint32_t missing = 0;
    auto final_vec = [&](int i) {
      uint32_t v[4], f[4], b[4];
      lds128(park + 16384 + i * 2048, v[0], v[1], v[2], v[3]);
      lds128(park + 6 * 16384 + i * 2048, f[0], f[1], f[2], f[3]); lds128(park + 7 * 16384 + i * 2048, b[0], b[1], b[2], b[3]);
      if (tag_bad(v[0], v[1], v[2], v[3], tag)) { missing |= 1u << i; v[0] = v[1] = v[2] = v[3] = 0; }
      #pragma unroll
      for (int e = 0; e < 4; e++) { const uint32_t t = add_bf16x2(f[e], v[e]); accU[i * 8 + 2 * e] = bf_lo(t) + bf_lo(b[e]); accU[i * 8 + 2 * e + 1] = bf_hi(t) + bf_hi(b[e]); }
    };
    #pragma unroll 1
    for (int u = 1; u < 7; u += 2) {
      run_pass<0, 5, 6>(accG, a, r, nop, nop);
      run_pass<1>(accU, a, r, nop, [&](int kb) { if (kb >= 1 && kb <= 4) store_vec(accG, u - 1, kb - 1, true); });
      run_pass<0, 0, 5>(accG, a, r, nop, [&](int kb) { if (kb >= 1) store_vec(accU, u, kb - 1, false); });
    }
    TSTAMP(5); GSTAMP(4);
    run_pass<0, 5, 6>(accG, a, r, nop, nop);
    run_pass<1>(accU, a, r, nop, [&](int kb) { if (kb >= 1 && kb <= 4) store_vec(accG, 6, kb - 1, false); if (kb == 5) fetch(5); });
    run_pass<0, 0, 5>(accG, a, r, nop, [&](int kb) {
      if (kb == 0) { wg_wait<0>(); store_vec(accU, 7, 0, false); store_vec(accU, 7, 1, false); }
      if (kb == 1) { store_vec(accU, 7, 2, false); store_vec(accU, 7, 3, false); fetch(6); }
      if (kb == 2) { mbar_wait(B_BASE, 0); mbar_wait(B_R, 0); cp_wait<1>(); }
      if (kb >= 2) final_vec(kb - 2);
      if (kb == 4) fetch(7); });
    r.ts = -1;
    {
      run_pass<0, 5, 6, false, true>(accG, a, r, nop, [&](int) { final_vec(3); });
      cp_wait<0>();
      #pragma unroll
      for (int i = 0; i < 4; i++) {
        uint32_t v[4], w[4]; lds128(park + i * 2048, w[0], w[1], w[2], w[3]); lds128(park + 5 * 16384 + i * 2048, v[0], v[1], v[2], v[3]);
        if (tag_bad(w[0], w[1], w[2], w[3], tag)) { missing |= 16u << i; w[0] = w[1] = w[2] = w[3] = 0; }
        if (tag_bad(v[0], v[1], v[2], v[3], tag)) { missing |= 256u << i; v[0] = v[1] = v[2] = v[3] = 0; }
        add_vec(accU + i * 8, add_bf16x2(v[0], w[0]), add_bf16x2(v[1], w[1]), add_bf16x2(v[2], w[2]), add_bf16x2(v[3], w[3]));
      }
      #pragma unroll 1
      for (int it = 0; missing && it < 4096; it++) {
        const int s = (__ffs(missing) - 1) >> 2;
        const uint4* src = (const uint4*)own_part(5 + s);
        uint32_t v[16];
        #pragma unroll
        for (int i = 0; i < 4; i++) ld_relaxed_v4(src + i * 128, v[i * 4], v[i * 4 + 1], v[i * 4 + 2], v[i * 4 + 3]);
        #pragma unroll
        for (int i = 0; i < 4; i++)
          if ((missing >> (4 * s + i) & 1) && !tag_bad(v[i * 4], v[i * 4 + 1], v[i * 4 + 2], v[i * 4 + 3], tag)) { add_vec(accU + i * 8, v[i * 4], v[i * 4 + 1], v[i * 4 + 2], v[i * 4 + 3]); missing &= ~(1u << (4 * s + i)); }
      }
      __syncwarp();
      wg_wait<0>();
      TSTAMP(6);
      #pragma unroll
      for (int i = 0; i < 32; i++) accU[i] += accG[i];
      const uint32_t pq = opaque(pk); const int lane = (pq >> 4) & 31, warp = (pq >> 9) & 3, wg = pq >> 13;
      const uint32_t stg = S_X + 4 * 16384 + wg * 8192 + warp * 2048;
      #pragma unroll
      for (int i = 0; i < 4; i++) {
        const int row = (lane & 7) + ((lane >> 3) & 1) * 8, chunk = 2 * i + (lane >> 4);
        asm volatile("stmatrix.sync.aligned.m8n8.x4.shared.b16 [%0], {%1,%2,%3,%4};" :: "r"(stg + row * 128 + ((chunk ^ (row & 7)) << 4)),
                     "r"(pack_bf16(accU[i * 8], accU[i * 8 + 1])), "r"(pack_bf16(accU[i * 8 + 2], accU[i * 8 + 3])), "r"(pack_bf16(accU[i * 8 + 4], accU[i * 8 + 5])), "r"(pack_bf16(accU[i * 8 + 6], accU[i * 8 + 7])) : "memory");
      }
      __syncwarp();
      TSTAMP(8);
      #pragma unroll
      for (int i = 0; i < 4; i++) {
        const int row = i * 4 + (lane >> 3), chunk = lane & 7;
        uint32_t o0, o1, o2, o3; lds128(stg + row * 128 + ((chunk ^ (row & 7)) << 4), o0, o1, o2, o3);
        *(uint4*)(out + (m * 128 + wg * 64 + warp * 16 + row) * D_ + j * 64 + chunk * 8) = make_uint4(o0, o1, o2, o3);
      }
    }
    }
    TSTAMP(7);
  }
}

typedef CUresult (*EncFn)(CUtensorMap*, CUtensorMapDataType, cuuint32_t, void*, const cuuint64_t*, const cuuint64_t*, const cuuint32_t*, const cuuint32_t*, CUtensorMapInterleave, CUtensorMapSwizzle, CUtensorMapL2promotion, CUtensorMapFloatOOBfill);
static void enc(EncFn f, CUtensorMap* tm, const void* base, int rank, uint64_t d0, uint64_t d1, uint64_t d2, uint64_t s1, uint64_t s2, uint32_t b0, uint32_t b1, uint32_t b2, CUtensorMapSwizzle sw) {
  cuuint64_t dims[3] = {d0, d1, d2}; cuuint64_t strides[2] = {s1, s2}; cuuint32_t box[3] = {b0, b1, b2}; cuuint32_t es[3] = {1, 1, 1};
  CUresult r = f(tm, CU_TENSOR_MAP_DATA_TYPE_BFLOAT16, rank, (void*)base, dims, strides, box, es, CU_TENSOR_MAP_INTERLEAVE_NONE, sw, CU_TENSOR_MAP_L2_PROMOTION_L2_128B, CU_TENSOR_MAP_FLOAT_OOB_FILL_NONE);
  if (r != CUDA_SUCCESS) fprintf(stderr, "tensor map encode failed %d\n", (int)r);
}

extern "C" void kernel_launch(void* const* d_in, const int* in_sizes, int n_in, void* d_out, int out_size) {
  static bool init = false;
  static Maps tm;
  if (!init) {
    void* fn = nullptr; cudaDriverEntryPointQueryResult st;
    cudaGetDriverEntryPoint("cuTensorMapEncodeTiled", &fn, cudaEnableDefault, &st);
    EncFn f = (EncFn)fn;
    void *xt, *yt; cudaGetSymbolAddress(&xt, g_xt); cudaGetSymbolAddress(&yt, g_yt);
    const CUtensorMapSwizzle S128 = CU_TENSOR_MAP_SWIZZLE_128B;
    enc(f, &tm.xraw3, d_in[0], 3, 64, L_, 9, D_ * 2, 128, 64, 16, 9, S128);
    enc(f, &tm.x2, d_in[0], 2, D_, L_, 1, D_ * 2, 0, 64, 128, 1, S128);
    enc(f, &tm.xt64, xt, 3, 64, D_ / 4, 128, 128, 32 * D_, 64, 16, 8, S128);
    enc(f, &tm.xt8, xt, 3, 64, D_ / 4, 128, 128, 32 * D_, 64, 2, 8, S128);
    enc(f, &tm.xt, xt, 2, 16 * D_, 128, 1, 32 * D_, 0, 64, 128, 1, S128);
    enc(f, &tm.yt, yt, 2, L_, D_, 1, L_ * 2, 0, 64, 64, 1, S128);
    enc(f, &tm.w1, d_in[10], 2, F_, D_, 1, F_ * 2, 0, 64, 96, 1, S128);
    enc(f, &tm.w3, d_in[11], 2, F_, D_, 1, F_ * 2, 0, 64, 96, 1, S128);
    enc(f, &tm.w2, d_in[12], 2, D_, F_, 1, D_ * 2, 0, 64, 96, 1, S128);
    enc(f, &tm.x8, d_in[0], 2, D_, L_, 1, D_ * 2, 0, 8, 128, 1, CU_TENSOR_MAP_SWIZZLE_NONE);
    enc(f, &tm.yt8, yt, 2, L_, D_, 1, L_ * 2, 0, 64, 8, 1, S128);
    cudaFuncSetAttribute(k_main, cudaFuncAttributeMaxDynamicSharedMemorySize, SMEM_BYTES);
    init = true;
  }
  SsmParams sp{(const __nv_bfloat16*)d_in[1], (const __nv_bfloat16*)d_in[2], (const __nv_bfloat16*)d_in[3], (const __nv_bfloat16*)d_in[4],
               (const __nv_bfloat16*)d_in[5], (const __nv_bfloat16*)d_in[6], (const __nv_bfloat16*)d_in[7]};
  k_main<<<NCTA, NTHR, SMEM_BYTES>>>(tm, sp, (const __nv_bfloat16*)d_in[8], (__nv_bfloat16*)d_out);
}
```

```cpp
#include <cuda_runtime.h>
#include <cuda.h>
#include <cuda_bf16.h>
#include <stdint.h>
#include <stdio.h>

__device__ __forceinline__ void wgmma_rs_n64_t1(float* d, uint32_t a0, uint32_t a1, uint32_t a2, uint32_t a3, uint64_t descB, int scaleD) {
  asm volatile("{\n.reg .pred p;\nsetp.ne.b32 p, %37, 0;\n"
    "wgmma.mma_async.sync.aligned.m64n64k16.f32.bf16.bf16 {%0,%1,%2,%3,%4,%5,%6,%7,%8,%9,%10,%11,%12,%13,%14,%15,%16,%17,%18,%19,%20,%21,%22,%23,%24,%25,%26,%27,%28,%29,%30,%31}, {%32,%33,%34,%35}, %36, p, 1, 1, 1;\n}\n"
    : "+f"(d[0]), "+f"(d[1]), "+f"(d[2]), "+f"(d[3]), "+f"(d[4]), "+f"(d[5]), "+f"(d[6]), "+f"(d[7]), "+f"(d[8]), "+f"(d[9]), "+f"(d[10]), "+f"(d[11]), "+f"(d[12]), "+f"(d[13]), "+f"(d[14]), "+f"(d[15]), "+f"(d[16]), "+f"(d[17]), "+f"(d[18]), "+f"(d[19]), "+f"(d[20]), "+f"(d[21]), "+f"(d[22]), "+f"(d[23]), "+f"(d[24]), "+f"(d[25]), "+f"(d[26]), "+f"(d[27]), "+f"(d[28]), "+f"(d[29]), "+f"(d[30]), "+f"(d[31])
    : "r"(a0), "r"(a1), "r"(a2), "r"(a3), "l"(descB), "r"(scaleD));
}
__device__ __forceinline__ void wgmma_ss_n48_t0(float* d, uint64_t descA, uint64_t descB, int scaleD) {
  asm volatile("{\n.reg .pred p;\nsetp.ne.b32 p, %26, 0;\n"
    "wgmma.mma_async.sync.aligned.m64n48k16.f32.bf16.bf16 {%0,%1,%2,%3,%4,%5,%6,%7,%8,%9,%10,%11,%12,%13,%14,%15,%16,%17,%18,%19,%20,%21,%22,%23}, %24, %25, p, 1, 1, 0, 0;\n}\n"
    : "+f"(d[0]), "+f"(d[1]), "+f"(d[2]), "+f"(d[3]), "+f"(d[4]), "+f"(d[5]), "+f"(d[6]), "+f"(d[7]), "+f"(d[8]), "+f"(d[9]), "+f"(d[10]), "+f"(d[11]), "+f"(d[12]), "+f"(d[13]), "+f"(d[14]), "+f"(d[15]), "+f"(d[16]), "+f"(d[17]), "+f"(d[18]), "+f"(d[19]), "+f"(d[20]), "+f"(d[21]), "+f"(d[22]), "+f"(d[23])
    : "l"(descA), "l"(descB), "r"(scaleD));
}
__device__ __forceinline__ void wgmma_rs_n32_t0(float* d, uint32_t a0, uint32_t a1, uint32_t a2, uint32_t a3, uint64_t descB, int scaleD) {
  asm volatile("{\n.reg .pred p;\nsetp.ne.b32 p, %21, 0;\n"
    "wgmma.mma_async.sync.aligned.m64n32k16.f32.bf16.bf16 {%0,%1,%2,%3,%4,%5,%6,%7,%8,%9,%10,%11,%12,%13,%14,%15}, {%16,%17,%18,%19}, %20, p, 1, 1, 0;\n}\n"
    : "+f"(d[0]), "+f"(d[1]), "+f"(d[2]), "+f"(d[3]), "+f"(d[4]), "+f"(d[5]), "+f"(d[6]), "+f"(d[7]), "+f"(d[8]), "+f"(d[9]), "+f"(d[10]), "+f"(d[11]), "+f"(d[12]), "+f"(d[13]), "+f"(d[14]), "+f"(d[15])
    : "r"(a0), "r"(a1), "r"(a2), "r"(a3), "l"(descB), "r"(scaleD));
}


#define SLPOS 2
#define PFLA 6
#define MAPMODE 0
#define PACE 300
#define BSPLIT 22
#define SENDV 0
#define RELPOS 6
constexpr int L_ = 2048, D_ = 576, F_ = 4608;
constexpr int NFFN = 128, NCTA = 132, NTHR = 384;
constexpr int STG_BYTES = 12288;
constexpr uint32_t S_X = 1024;
constexpr uint32_t S_RING = S_X + 147456;
constexpr uint32_t S_MISC = S_RING + 6 * STG_BYTES;
constexpr uint32_t S_BAR = S_MISC + 8320, S_DSK = S_BAR + 512, S_DUMMY = S_DSK + 256;
constexpr int SMEM_BYTES = S_DUMMY + 256 + 768 - 1024;
constexpr uint32_t B_FULL = S_BAR, B_EMPTY = S_BAR + 64, B_X = S_BAR + 128  , B_PFREE = S_BAR + 176, B_BASE = S_BAR + 184  ,
                   B_RAW = S_BAR + 200, B_LN = S_BAR + 208, B_U = S_BAR + 216  , B_KDONE = S_BAR + 232  , B_CDONE = S_BAR + 248  ,
                   B_RDONE = S_BAR + 264  , B_H = S_BAR + 280, B_YDONE = S_BAR + 288, B_PP = S_BAR + 296  , B_GO = S_BAR + 312, B_PUB = S_BAR + 320  , B_R = S_BAR + 344, B_H8 = S_BAR + 352, B_EP = S_BAR + 360, B_LN2 = S_BAR + 368;
constexpr uint32_t S_LN = S_RING + 3 * STG_BYTES;
constexpr uint32_t S_U = S_LN + 20480;
__device__ __forceinline__ uint32_t s_w_of(int ch) { return ch < 2 ? S_LN + ch * 8256 : (ch == 2 ? S_X + 8 * 16384 : S_MISC); }
__host__ __device__ constexpr int xslot(int kb) { return kb < 3 ? kb : (kb < 6 ? kb + 1 : (kb == 6 ? 3 : kb)); }

__device__ __nv_bfloat16 g_xt[D_ * L_];
__device__ __nv_bfloat16 g_yt[D_ * L_];
__device__ uint4 g_part[16 * 8 * 3 * 1024];
__device__ uint4 g_acc[16 * 9 * 1024];
__device__ unsigned int g_cnt_acc[16 * 9 * 8];
__device__ unsigned int g_ticket, g_cnt_all, g_cnt_y, g_cnt_ys;

__device__ __forceinline__ uint32_t smem_u32(const void* p) { return (uint32_t)__cvta_generic_to_shared(p); }
__device__ __forceinline__ void mbar_init(uint32_t bar, uint32_t cnt) { asm volatile("mbarrier.init.shared::cta.b64 [%0], %1;" :: "r"(bar), "r"(cnt)); }
__device__ __forceinline__ void mbar_expect_tx(uint32_t bar, uint32_t bytes) { asm volatile("mbarrier.arrive.expect_tx.shared::cta.b64 _, [%0], %1;" :: "r"(bar), "r"(bytes) : "memory"); }
__device__ __forceinline__ void mbar_arrive(uint32_t bar) { asm volatile("mbarrier.arrive.shared::cta.b64 _, [%0];" :: "r"(bar) : "memory"); }
__device__ __forceinline__ bool mbar_try_wait(uint32_t bar, uint32_t parity) {
  uint32_t ok;
  asm volatile("{\n.reg .pred p;\nmbarrier.try_wait.parity.shared::cta.b64 p, [%1], %2;\nselp.u32 %0, 1, 0, p;\n}\n" : "=r"(ok) : "r"(bar), "r"(parity) : "memory");
  return ok;
}
__device__ __forceinline__ void mbar_wait(uint32_t bar, uint32_t parity) {
  asm volatile("{\n.reg .pred p;\n.reg .u32 c;\nmov.u32 c, 0;\n"
               "WAIT_LOOP:\nmbarrier.try_wait.parity.shared::cta.b64 p, [%0], %1;\nadd.u32 c, c, 1;\n@!p setp.gt.u32 p, c, 8192;\n@!p bra WAIT_LOOP;\n}\n" :: "r"(bar), "r"(parity) : "memory");
}
__device__ __forceinline__ void mbar_wait_long(uint32_t bar, uint32_t parity) {
  asm volatile("{\n.reg .pred p;\n.reg .u32 t0, t1;\nmov.u32 t0, %%clock;\n"
               "WAIT_LOOP:\nmbarrier.try_wait.parity.shared::cta.b64 p, [%0], %1;\nmov.u32 t1, %%clock;\nsub.u32 t1, t1, t0;\n@!p setp.gt.u32 p, t1, 0x800000;\n@!p bra WAIT_LOOP;\n}\n" :: "r"(bar), "r"(parity) : "memory");
}
__device__ __forceinline__ void mbar_spin(uint32_t bar, uint32_t parity) {
  asm volatile("{\n.reg .pred p;\n.reg .u32 c;\nmov.u32 c, 0;\n"
               "SPIN_LOOP:\nmbarrier.test_wait.parity.shared::cta.b64 p, [%0], %1;\nadd.u32 c, c, 1;\n@!p setp.gt.u32 p, c, 0x100000;\n@!p bra SPIN_LOOP;\n}\n" :: "r"(bar), "r"(parity) : "memory");
}
__device__ __forceinline__ void flag_wait(const unsigned int* f, unsigned int val, unsigned int ns) {
  unsigned int v;
  #pragma unroll 1
  for (int it = 0; it < 16384; it++) {
    asm volatile("ld.relaxed.gpu.global.u32 %0, [%1];" : "=r"(v) : "l"(f) : "memory");
    if (v == val) break;
    __nanosleep(ns);
  }
  asm volatile("ld.acquire.gpu.global.u32 %0, [%1];" : "=r"(v) : "l"(f) : "memory");
}
__device__ __forceinline__ void red_add(unsigned int* p) { asm volatile("red.relaxed.gpu.global.add.u32 [%0], 1;" :: "l"(p) : "memory"); }
__device__ __forceinline__ void fence_gpu() { asm volatile("fence.acq_rel.gpu;" ::: "memory"); }
__device__ __forceinline__ void fence_async() { asm volatile("fence.proxy.async.global;" ::: "memory"); }
__device__ __forceinline__ void fence_async_smem() { asm volatile("fence.proxy.async.shared::cta;" ::: "memory"); }
__device__ __forceinline__ unsigned int cur_epoch() { mbar_wait(B_EP, 0); unsigned int v; asm volatile("ld.shared.b32 %0, [%1];" : "=r"(v) : "r"(S_DSK + 196) : "memory"); return v; }
__device__ __forceinline__ void tma2d(uint32_t dst, const CUtensorMap* tm, int c0, int c1, uint32_t bar) {
  asm volatile("cp.async.bulk.tensor.2d.shared::cluster.global.mbarrier::complete_tx::bytes [%0], [%1, {%3, %4}], [%2];" :: "r"(dst), "l"(tm), "r"(bar), "r"(c0), "r"(c1) : "memory");
}
__device__ __forceinline__ void tma3d(uint32_t dst, const CUtensorMap* tm, int c0, int c1, int c2, uint32_t bar) {
  asm volatile("cp.async.bulk.tensor.3d.shared::cluster.global.mbarrier::complete_tx::bytes [%0], [%1, {%3, %4, %5}], [%2];" :: "r"(dst), "l"(tm), "r"(bar), "r"(c0), "r"(c1), "r"(c2) : "memory");
}
__device__ __forceinline__ void bulk_g2s(uint32_t dst, const void* src, uint32_t bytes, uint32_t bar) {
  asm volatile("cp.async.bulk.shared::cluster.global.mbarrier::complete_tx::bytes [%0], [%1], %2, [%3];" :: "r"(dst), "l"(src), "r"(bytes), "r"(bar) : "memory");
}
__device__ __forceinline__ void prefetch_tmap(const CUtensorMap* tm) { asm volatile("prefetch.tensormap [%0];" :: "l"(tm) : "memory"); }
__device__ __forceinline__ void wg_fence() { asm volatile("wgmma.fence.sync.aligned;" ::: "memory"); }
__device__ __forceinline__ void wg_commit() { asm volatile("wgmma.commit_group.sync.aligned;" ::: "memory"); }
template <int N> __device__ __forceinline__ void wg_wait() { asm volatile("wgmma.wait_group.sync.aligned %0;" :: "n"(N) : "memory"); }
__device__ __forceinline__ void bar_sync(int id, int n) { asm volatile("bar.sync %0, %1;" :: "r"(id), "r"(n) : "memory"); }
__device__ __forceinline__ void bar_arrive(int id, int n) { asm volatile("bar.arrive %0, %1;" :: "r"(id), "r"(n) : "memory"); }
__device__ __forceinline__ uint32_t pack_bf16(float lo, float hi) { uint32_t r; asm("cvt.rn.bf16x2.f32 %0, %1, %2;" : "=r"(r) : "f"(hi), "f"(lo)); return r; }
__device__ __forceinline__ float bf_lo(uint32_t v) { return __uint_as_float(v << 16); }
__device__ __forceinline__ float bf_hi(uint32_t v) { return __uint_as_float(v & 0xFFFF0000u); }
__device__ __forceinline__ float bf_round(float v) { return bf_lo(pack_bf16(v, v)); }
__device__ __forceinline__ uint32_t mul_bf16x2(uint32_t a, uint32_t b) { uint32_t r; asm("mul.rn.bf16x2 %0, %1, %2;" : "=r"(r) : "r"(a), "r"(b)); return r; }
__device__ __forceinline__ uint32_t add_bf16x2(uint32_t a, uint32_t b) { uint32_t r; asm("add.rn.bf16x2 %0, %1, %2;" : "=r"(r) : "r"(a), "r"(b)); return r; }
__device__ __forceinline__ uint32_t sub_bf16x2(uint32_t a, uint32_t b) { uint32_t r; asm("sub.rn.bf16x2 %0, %1, %2;" : "=r"(r) : "r"(a), "r"(b)); return r; }
__device__ __forceinline__ void ldsm_x4(uint32_t addr, uint32_t& r0, uint32_t& r1, uint32_t& r2, uint32_t& r3) {
  asm volatile("ldmatrix.sync.aligned.m8n8.x4.shared.b16 {%0,%1,%2,%3}, [%4];" : "=r"(r0), "=r"(r1), "=r"(r2), "=r"(r3) : "r"(addr) : "memory");
}
__device__ __forceinline__ void ldsm_x4t(uint32_t addr, uint32_t& r0, uint32_t& r1, uint32_t& r2, uint32_t& r3) {
  asm volatile("ldmatrix.sync.aligned.m8n8.x4.trans.shared.b16 {%0,%1,%2,%3}, [%4];" : "=r"(r0), "=r"(r1), "=r"(r2), "=r"(r3) : "r"(addr) : "memory");
}
__device__ __forceinline__ float silu_f(float g) {
  const float hh = 0.5f * g; float th; asm("tanh.approx.f32 %0, %1;" : "=f"(th) : "f"(hh)); return fmaf(hh, th, hh);
  float e; asm("ex2.approx.ftz.f32 %0, %1;" : "=f"(e) : "f"(g * -1.4426950408889634f));
  float r; asm("rcp.approx.ftz.f32 %0, %1;" : "=f"(r) : "f"(1.0f + e));
  return g * r;
}
__device__ __forceinline__ void sts128(uint32_t addr, uint32_t a, uint32_t b, uint32_t c, uint32_t d) { asm volatile("st.shared.v4.b32 [%0], {%1,%2,%3,%4};" :: "r"(addr), "r"(a), "r"(b), "r"(c), "r"(d) : "memory"); }
__device__ __forceinline__ void sts64(uint32_t addr, uint32_t a, uint32_t b) { asm volatile("st.shared.v2.b32 [%0], {%1,%2};" :: "r"(addr), "r"(a), "r"(b) : "memory"); }
__device__ __forceinline__ void sts32(uint32_t addr, uint32_t a) { asm volatile("st.shared.b32 [%0], %1;" :: "r"(addr), "r"(a) : "memory"); }
__device__ __forceinline__ void lds128(uint32_t addr, uint32_t& a, uint32_t& b, uint32_t& c, uint32_t& d) { asm volatile("ld.shared.v4.b32 {%0,%1,%2,%3}, [%4];" : "=r"(a), "=r"(b), "=r"(c), "=r"(d) : "r"(addr) : "memory"); }
__device__ __forceinline__ void lds64(uint32_t addr, uint32_t& a, uint32_t& b) { asm volatile("ld.shared.v2.b32 {%0,%1}, [%2];" : "=r"(a), "=r"(b) : "r"(addr) : "memory"); }
__device__ __forceinline__ uint32_t lds32(uint32_t addr) { uint32_t a; asm volatile("ld.shared.b32 %0, [%1];" : "=r"(a) : "r"(addr) : "memory"); return a; }
__device__ __forceinline__ float ldsf(uint32_t addr) { float a; asm volatile("ld.shared.f32 %0, [%1];" : "=f"(a) : "r"(addr) : "memory"); return a; }
__device__ __forceinline__ uint32_t opaque(uint32_t v) { uint32_t r; asm volatile("mov.b32 %0, %1;" : "=r"(r) : "r"(v)); return r; }
__device__ __forceinline__ void cp_async16(uint32_t dst, const void* src) { asm volatile("cp.async.cg.shared.global [%0], [%1], 16;" :: "r"(dst), "l"(src) : "memory"); }
__device__ __forceinline__ void cp_commit() { asm volatile("cp.async.commit_group;" ::: "memory"); }
template <int N> __device__ __forceinline__ void cp_wait() { asm volatile("cp.async.wait_group %0;" :: "n"(N) : "memory"); }
__device__ __forceinline__ void st_relaxed_v4(uint4* p, uint32_t a, uint32_t b, uint32_t c, uint32_t d) {
  asm volatile("st.relaxed.gpu.global.v4.b32 [%0], {%1,%2,%3,%4};" :: "l"(p), "r"(a), "r"(b), "r"(c), "r"(d) : "memory");
}
__device__ __forceinline__ void ld_relaxed_v4(const uint4* p, uint32_t& a, uint32_t& b, uint32_t& c, uint32_t& d) {
  asm volatile("ld.relaxed.gpu.global.v4.b32 {%0,%1,%2,%3}, [%4];" : "=r"(a), "=r"(b), "=r"(c), "=r"(d) : "l"(p) : "memory");
}
__device__ __forceinline__ bool tag_bad(uint32_t a, uint32_t b, uint32_t c, uint32_t d, uint32_t tag) { return (((a ^ tag) | (b ^ tag) | (c ^ tag) | (d ^ tag)) & 1u) != 0; }
__device__ __forceinline__ void poll_v4(const uint4* p, uint32_t& a, uint32_t& b, uint32_t& c, uint32_t& d, uint32_t tag) {
  int it = 0;
  do { ld_relaxed_v4(p, a, b, c, d); } while (tag_bad(a, b, c, d, tag) && ++it < 4096);
}
__device__ __forceinline__ void add_vec(float* f, uint32_t v0, uint32_t v1, uint32_t v2, uint32_t v3) {
  f[0] += bf_lo(v0); f[1] += bf_hi(v0); f[2] += bf_lo(v1); f[3] += bf_hi(v1); f[4] += bf_lo(v2); f[5] += bf_hi(v2); f[6] += bf_lo(v3); f[7] += bf_hi(v3);
}

struct cplx { float re, im; };
__device__ __forceinline__ cplx cmul(cplx a, cplx b) { return {fmaf(a.re, b.re, -a.im * b.im), fmaf(a.re, b.im, a.im * b.re)}; }
__device__ __forceinline__ cplx cexp_f(float ar, float ai) {
  float mag; asm("ex2.approx.f32 %0, %1;" : "=f"(mag) : "f"(ar * 1.4426950408889634f));
  const float k = rintf(ai * 0.15915494309189535f);
  float r = fmaf(ai, 0.15915494309189535f, -k);
  r = fmaf(ai, 6.4206383e-9f, r);
  r *= 6.283185307179586f;
  float sn, cs; asm("sin.approx.f32 %0, %1;" : "=f"(sn) : "f"(r)); asm("cos.approx.f32 %0, %1;" : "=f"(cs) : "f"(r));
  return {mag * cs, mag * sn};
}
__device__ __forceinline__ float bf2f(__nv_bfloat16 v) { return __bfloat162float(v); }

constexpr int KG_B = 32768, KG_TAB = 2688;

struct SsmParams { const __nv_bfloat16 *are, *aim, *bre, *bim, *cre, *cim, *logdt; };
struct ModeRaw { uint32_t are, aim, bre, bim, cre, cim; __nv_bfloat16 ldt; };
__device__ __forceinline__ ModeRaw load_mode(const SsmParams& p, int d, int t128) {
  const int o = d * 64 + t128;
  auto ld = [&](const __nv_bfloat16* b) { return __ldg((const uint32_t*)b + o); };
  return {ld(p.are), ld(p.aim), ld(p.bre), ld(p.bim), ld(p.cre), ld(p.cim), __ldg(p.logdt + d + (t128 >> 6))};
}

__device__ __forceinline__ void layer_norm16(int tid_);
__device__ __forceinline__ void kgen_powers(const ModeRaw& mr, int wg, int t128_, int row0, bool g_first) {
  const int t128 = opaque(t128_);
  const uint32_t scr = S_X + wg * 65536;
  const int warp = t128 >> 5, lane = t128 & 31;
  cplx cb[2], z1[2], zq[2];
  const float dt = bf_round(expf(bf2f(mr.ldt)));
  #pragma unroll
  for (int c = 0; c < 2; c++) {
    auto f = [&](uint32_t v) { return c ? bf_hi(v) : bf_lo(v); };
    const float ar = dt * f(mr.are), ai = dt * f(mr.aim);
    cb[c] = cmul({f(mr.cre), f(mr.cim)}, {dt * f(mr.bre), dt * f(mr.bim)});
    z1[c] = cexp_f(ar, ai); zq[c] = cexp_f(ar * 256.f, ai * 256.f);
  }
  uint32_t ad[8];
  #pragma unroll
  for (int i = 0; i < 8; i++) ad[i] = scr + KG_B + ((warp & 1) * 2 + (lane >> 4)) * 6144 + (warp >> 1) * 3072 + (lane & 1) * 8 + ((((lane >> 1) & 7) ^ i) << 4);
  cplx z2[2];
  {
    auto put = [&](int b, const cplx* v) { sts64(ad[b & 7] + b * 128, pack_bf16(v[0].re, -v[0].im), pack_bf16(v[1].re, -v[1].im)); };
    cplx e[2], o[2], h[2], h0[2], h4[2];
    #pragma unroll
    for (int c = 0; c < 2; c++) { z2[c] = cmul(z1[c], z1[c]); e[c] = cb[c]; o[c] = cmul(cb[c], z1[c]); }
    #pragma unroll
    for (int i = 0; i < 4; i++) {
      put(2 * i, e); put(2 * i + 1, o);
      #pragma unroll
      for (int c = 0; c < 2; c++) {
        h[c] = cmul(e[c], zq[c]);
        if (i == 0) h0[c] = h[c];
        if (i == 2) h4[c] = h[c];
        if (i < 3) { e[c] = cmul(e[c], z2[c]); o[c] = cmul(o[c], z2[c]); }
      }
      put(8 + i, h);
    }
    #pragma unroll
    for (int i = 0; i < 7; i++) {
      #pragma unroll
      for (int c = 0; c < 2; c++) { h0[c] = cmul(h0[c], zq[c]); if (i < 2) h4[c] = cmul(h4[c], zq[c]); }
      put(i < 2 ? 12 + 2 * i : 14 + i, h0);
      if (i < 2) put(13 + 2 * i, h4);
    }
  }
  if (row0 >= 0) layer_norm16(wg * 128 + t128);
  {
    #pragma unroll
    for (int i = 0; i < 8; i++) ad[i] += ((warp & 1) * 2 + (lane >> 4)) * 2048 + (warp >> 1) * 1024 - KG_B;
    cplx y[2][2], z16[2];
    #pragma unroll
    for (int c = 0; c < 2; c++) { const cplx z4 = cmul(z2[c], z2[c]); y[0][c] = {1.f, 0.f}; y[1][c] = cmul(z4, z4); z16[c] = cmul(y[1][c], y[1][c]); }
    #pragma unroll 1
    for (int jo = 0; jo < 4096; jo += 1024) {
      #pragma unroll
      for (int jj = 0; jj < 8; jj++) {
        sts64(ad[jj] + jo + jj * 128, pack_bf16(y[jj & 1][0].re, y[jj & 1][0].im), pack_bf16(y[jj & 1][1].re, y[jj & 1][1].im));
        #pragma unroll
        for (int c = 0; c < 2; c++) y[jj & 1][c] = cmul(y[jj & 1][c], z16[c]);
      }
    }
  }
  fence_async_smem();
}
__device__ __forceinline__ void kgen_finish(int wg, int t128_, bool ln, bool g_first) {
  const int t128 = opaque(t128_);
  const uint32_t scr = S_X + wg * 65536;
  const int warp = t128 >> 5, lane = t128 & 31;
  bar_sync(2 + wg, 128);
  float dd[24];
  {
    wg_fence();
    const uint64_t da = ((uint64_t)0x40000040u << 32) | opaque((scr >> 4) | 0x10000u), db = da + KG_B / 16;
    #pragma unroll
    for (int ks = 0; ks < 16; ks++) wgmma_ss_n48_t0(dd, da + (ks >> 2) * 512 + (ks & 3) * 2, db + (ks >> 2) * 384 + (ks & 3) * 2, ks != 0);
    wg_commit();
    wg_wait<0>();
  }
  bar_sync(2 + wg, 128);
  {
    const int g = lane >> 2, q = lane & 3, hi = warp >> 1;
    const uint32_t tb = scr + hi * KG_TAB;
    #pragma unroll
    for (int rr = 0; rr < 2; rr++) {
      const int jj = (warp & 1) * 16 + g + rr * 8;
      float v[6];
      #pragma unroll
      for (int b = 0; b < 3; b++) { v[b * 2] = hi ? dd[12 + b * 4 + rr * 2] : dd[b * 4 + rr * 2]; v[b * 2 + 1] = hi ? dd[12 + b * 4 + rr * 2 + 1] : dd[b * 4 + rr * 2 + 1]; }
      sts64(tb + (8 * jj + 2 * q) * 4, __float_as_uint(v[0]), __float_as_uint(v[1]));
      sts64(tb + (q < 2 ? 256 + 4 * jj + 2 * q : 256 + 64 * q + 2 * jj) * 4, __float_as_uint(v[2]), __float_as_uint(v[3]));
      if (q < 2) { sts32(tb + (512 + 64 * q + jj) * 4, __float_as_uint(v[4])); sts32(tb + (544 + 64 * q + jj) * 4, __float_as_uint(v[5])); }
      else if (q == 2 && jj == 0) sts32(tb + 640 * 4, __float_as_uint(v[4]));
    }
  }
  if (ln && wg == 0) mbar_wait(B_LN2, 0);
  bar_sync(2 + wg, 128);
  #pragma unroll
  for (int c = 0; c < 2; c++) {
    const uint32_t t0 = scr + c * KG_TAB, wp = s_w_of(wg * 2 + c) + 64 + t128 * 16;
    const int t = t128;
    float k0, k1, k2, k3, kp;
    if (warp < 2) {
      uint32_t a0, a1, a2, a3; lds128(t0 + 16 * t, a0, a1, a2, a3);
      k0 = __uint_as_float(a0); k1 = __uint_as_float(a1); k2 = __uint_as_float(a2); k3 = __uint_as_float(a3);
      kp = ldsf(t0 + 16 * t - (t ? 4 : 0)); if (t == 0) kp = 0.f;
    } else {
      uint32_t a0, a1; lds64(t0 + (128 + 2 * t) * 4, a0, a1);
      k0 = k1 = __uint_as_float(a0); k2 = __uint_as_float(a1); k3 = ldsf(t0 + (130 + 2 * t) * 4);
      kp = ldsf(t0 + (t == 64 ? 255 : 128 + 2 * t) * 4);
    }
    const float s0 = ldsf(t0 + (384 + t) * 4), s1 = ldsf(t0 + (385 + t) * 4);
    const int ph = t & 3, b3 = 512 + 2 * (t >> 2);
    const float a0 = ldsf(t0 + (b3 + (ph >> 1)) * 4), c0 = ldsf(t0 + (b3 + ((ph + 1) >> 1)) * 4);
    const float a1 = ldsf(t0 + (b3 + 64 + (ph >> 1)) * 4), c1 = ldsf(t0 + (b3 + 64 + ((ph + 1) >> 1)) * 4);
    sts128(wp, pack_bf16(k0, kp), pack_bf16(k1, k0), pack_bf16(k2, k1), pack_bf16(k3, k2));
    const float m = (t & 1) ? s1 : s0;
    sts128(wp + 2048, pack_bf16(s0, s0), pack_bf16(s0, s0), pack_bf16(m, s0), pack_bf16(s1, m));
    const float f0 = ph == 1 ? a0 : c0, f1 = ph == 1 ? a1 : c1;
    sts128(wp + 4096, pack_bf16(f0, a0), pack_bf16(c0, f0), pack_bf16(c0, c0), pack_bf16(c0, c0));
    sts128(wp + 6144, pack_bf16(f1, a1), pack_bf16(c1, f1), pack_bf16(c1, c1), pack_bf16(c1, c1));
    if (t < 4) sts128(wp - 64, 0, 0, 0, 0);
    if (!ln && t < 112) sts128(S_U - 3584 + c * 1792 + t * 16, 0, 0, 0, 0);
  }
}

template <int P> __device__ __forceinline__ void conv_step(float* acc, const uint32_t* fr, uint32_t db) {
  uint32_t lo; asm volatile("sub.u32 %0, %1, %2;" : "=r"(lo) : "r"(db), "n"(32 * P - 256 * 3));
  uint64_t d = ((uint64_t)0x40000040u << 32) | lo;
  #pragma unroll
  for (int sg = 3; sg >= P / 8; sg--) wgmma_rs_n32_t0(acc + 16 * sg, fr[0], fr[1], fr[2], fr[3], d - 256 * (3 - sg), P != 0);
}
template <int I, int I1> struct ConvPairs {
  static __device__ __forceinline__ void run(float* acc, const uint32_t* fr, uint32_t db) {
    conv_step<I>(acc, fr + I * 4, db); conv_step<31 - I>(acc, fr + (31 - I) * 4, db);
    ConvPairs<I + 1, I1>::run(acc, fr, db);
  }
};
template <int I1> struct ConvPairs<I1, I1> { static __device__ __forceinline__ void run(float*, const uint32_t*, uint32_t) {} };

__device__ __forceinline__ void conv_reduce(uint32_t s_r, int t128, __nv_bfloat16* yrow) {
  #pragma unroll
  for (int h = 0; h < 2; h++) {
    const int cc = t128 + h * 128;
    uint32_t v[4][4];
    #pragma unroll
    for (int b = 0; b < 4; b++) {
      lds128(s_r + b * 4096 + cc * 16, v[b][0], v[b][1], v[b][2], v[b][3]);
      if (h == 0 && b > (cc >> 1)) { v[b][0] = v[b][1] = v[b][2] = v[b][3] = 0; }
    }
    uint32_t o[4];
    #pragma unroll
    for (int e = 0; e < 4; e++) { const uint32_t p = add_bf16x2(v[0][e], v[1][e]), q = add_bf16x2(v[2][e], v[3][e]); o[e] = add_bf16x2(p, q); }
    *(uint4*)(yrow + cc * 8) = make_uint4(o[0], o[1], o[2], o[3]);
  }
}
__device__ __forceinline__ void conv_one(int wg, int c, int t128_, int uphase, __nv_bfloat16* y0) {
  const int t128 = opaque(t128_), ch = wg * 2 + c;
  const uint32_t s_w = s_w_of(ch), s_r = S_X + wg * 65536 + 49152;
  const int warp = t128 >> 5, lane = t128 & 31;
  float acc[64];
  uint32_t fr[128];
  const uint32_t wa = s_w + 64 + (warp * 16 + (lane >> 2) - 2 * (lane & 3)) * 4;
  const uint32_t zero = lds32(s_w);
  auto ld = [&](int p) { fr[p * 4] = lds32(wa + p * 256); fr[p * 4 + 1] = lds32(wa + p * 256 + 32); fr[p * 4 + 2] = lds32(wa + p * 256 - 32);
                         asm volatile("xor.b32 %0, %1, %2;" : "=r"(fr[p * 4 + 3]) : "r"(fr[p * 4]), "r"(zero)); };
  const uint32_t db = ((S_U >> 4) | 0x10000u) + ch * 2;
  #pragma unroll
  for (int p = 0; p < 32; p++) ld(p);
  if (c == 0) mbar_wait(B_U, uphase);
  mbar_wait(B_PP + 8 * wg, wg ? c ^ 1 : c);
  wg_fence();
  ConvPairs<0, 16>::run(acc, fr, db);
  wg_commit();
  if (lane == 0) mbar_arrive(B_PP + 8 - 8 * wg);
  if (c == 1) conv_reduce(s_r, t128, y0);
  wg_wait<0>();
  if (c == 1 && lane == 0) mbar_arrive(B_CDONE);
  if (c == 1) bar_sync(2 + wg, 128);
  const int col = 8 * (lane >> 4) + (lane & 7) + warp;
  const uint32_t ra = s_r + warp * 4096 + (col * 16 + ((lane >> 3) & 1) * 8) * 2;
  #pragma unroll
  for (int v = 0; v < 8; v++)
    asm volatile("stmatrix.sync.aligned.m8n8.x4.trans.shared.b16 [%0], {%1,%2,%3,%4};" :: "r"((v == 7 && col >= 16) ? S_DUMMY : ra + v * 512),
                 "r"(pack_bf16(acc[v * 8], acc[v * 8 + 1])), "r"(pack_bf16(acc[v * 8 + 2], acc[v * 8 + 3])), "r"(pack_bf16(acc[v * 8 + 4], acc[v * 8 + 5])), "r"(pack_bf16(acc[v * 8 + 6], acc[v * 8 + 7])) : "memory");
  bar_sync(2 + wg, 128);
}

__device__ __forceinline__ void layer_norm16(int tid_) {
  const int tid = opaque(tid_), row = tid >> 4, l16 = tid & 15;
  const uint32_t ra = S_LN + (l16 >> 3) * 2048 + row * 128 + (((l16 & 7) ^ (row & 7)) << 4);
  uint32_t v[20];
  mbar_wait(B_RAW, 0);
  #pragma unroll
  for (int i = 0; i < 4; i++) lds128(ra + i * 4096, v[i * 4], v[i * 4 + 1], v[i * 4 + 2], v[i * 4 + 3]);
  v[16] = v[17] = v[18] = v[19] = 0;
  if (l16 < 8) lds128(ra + 16384, v[16], v[17], v[18], v[19]);
  float s0 = 0.f, s1 = 0.f, q0 = 0.f, q1 = 0.f;
  #pragma unroll
  for (int e = 0; e < 20; e++) { const float lo = bf_lo(v[e]), hi = bf_hi(v[e]); s0 += lo; s1 += hi; q0 = fmaf(lo, lo, q0); q1 = fmaf(hi, hi, q1); }
  float s = s0 + s1, ss = q0 + q1;
  #pragma unroll
  for (int o = 8; o; o >>= 1) { s += __shfl_xor_sync(0xffffffffu, s, o); ss += __shfl_xor_sync(0xffffffffu, ss, o); }
  const float mean = s * (1.f / D_), var = fmaxf(fmaf(-mean, mean, ss * (1.f / D_)), 0.f);
  const uint32_t mb = pack_bf16(mean, mean);
  const float rs = 1.0f / bf_round(sqrtf(bf_round(bf_round(var) + 1e-5f)));
  const uint32_t rh = pack_bf16(rs, rs), rl = pack_bf16(rs - bf_lo(rh), rs - bf_lo(rh));
  #pragma unroll
  for (int e = 0; e < 20; e++) { const uint32_t dd = sub_bf16x2(v[e], mb); asm("fma.rn.bf16x2 %0, %1, %2, %3;" : "=r"(v[e]) : "r"(dd), "r"(rh), "r"(mul_bf16x2(dd, rl))); }
  #pragma unroll
  for (int i = 0; i < 5; i++) if (i < 4 || l16 < 8) sts128(ra + i * 4096, v[i * 4], v[i * 4 + 1], v[i * 4 + 2], v[i * 4 + 3]);
  bar_sync(4, 256);
  {
    const int warp = tid >> 5, lane = tid & 31, r = lane & 7, e = lane >> 3, tok = (r >> 1) * 4 + (r & 1) + (e & 1) * 2;
    const uint32_t la = S_LN + (warp >> 2) * 2048 + tok * 128 + ((((warp & 3) * 2 + (e >> 1)) ^ (tok & 7)) << 4), ta = S_LN + 18432 + warp * 512 + lane * 8;
    #pragma unroll
    for (int i = 0; i < 5; i++) if (i < 4 || warp < 4) ldsm_x4t(la + i * 4096, v[i * 4], v[i * 4 + 1], v[i * 4 + 2], v[i * 4 + 3]);
    #pragma unroll
    for (int i = 0; i < 5; i++) if (i < 4 || warp < 4) { sts64(ta + i * 4096, v[i * 4], v[i * 4 + 1]); sts64(ta + i * 4096 + 256, v[i * 4 + 2], v[i * 4 + 3]); }
  }
  fence_async_smem();
  __syncwarp();
  if ((tid & 31) == 0) mbar_arrive(B_LN);
}

__device__ __forceinline__ void ssm_phase(const SsmParams& p, ModeRaw mr, int wg, int d0, int npair, int row0, int t128) {
  int d = d0 + wg * 2;
  #pragma unroll 1
  for (int it = 0; it < npair; it++, d += 4) {
    kgen_powers(mr, wg, t128, row0, it == 0);
    kgen_finish(wg, t128, row0 >= 0, it == 0);
    fence_async_smem();
    __syncwarp();
    if ((t128 & 31) == 0) mbar_arrive(B_KDONE + 8 * wg);
    bar_sync(2 + wg, 128);
    #pragma unroll 1
    for (int c = 0; c < 2; c++) conv_one(wg, c, t128, it & 1, g_yt + d * L_);
    conv_reduce(S_X + wg * 65536 + 49152, opaque(t128), g_yt + (d + 1) * L_);
    fence_async_smem();
    __syncwarp();
    if ((t128 & 31) == 0) mbar_arrive(B_RDONE + 8 * wg);
    if (it + 1 < npair) { mr = load_mode(p, d + 4, t128); bar_sync(4, 256); }
  }
  if ((t128 & 31) == 0) mbar_arrive(B_YDONE);
}

struct Ring { bool ready; int ts; unsigned int wt; };
__device__ __forceinline__ void arrive_one(uint32_t bar) {
  asm volatile("{\n.reg .pred p;\nelect.sync _|p, 0xffffffff;\n@p mbarrier.arrive.shared::cta.b64 _, [%0];\n}\n" :: "r"(bar) : "memory");
}

template <int PH, int KB0 = 0, int KB1 = 6, bool FIRST = false, bool LAST = false, class Pre, class Slice>
__device__ __forceinline__ void run_pass(float* acc, uint32_t* a, Ring& r, Pre pre, Slice slice) {
  #pragma unroll
  for (int kb = KB0; kb < KB1; kb++) {
    pre(kb);
    if (!r.ready) mbar_wait(B_FULL + 8 * kb, PH);
    wg_fence();
    const uint64_t d0 = ((uint64_t)0x40000040u << 32) | ((S_RING + kb * STG_BYTES) >> 4) | (512u << 16);
    #pragma unroll
    for (int kk = 0; kk < 6; kk++) {
      wgmma_rs_n64_t1(acc, a[(kb * 6 + kk) * 4 + 0], a[(kb * 6 + kk) * 4 + 1], a[(kb * 6 + kk) * 4 + 2], a[(kb * 6 + kk) * 4 + 3], d0 + kk * 128, (kb | kk) != 0);
      if (kk == RELPOS && (kb > 0 || !FIRST)) { wg_wait<0>(); arrive_one(B_EMPTY + 8 * ((kb + 5) % 6)); }
      if (kk == SLPOS) slice(kb);
    }
    wg_commit();
    if (!LAST) r.ready = mbar_try_wait(B_FULL + 8 * ((kb + 1) % 6), kb == 5 ? PH ^ 1 : PH);
    if (SLPOS >= 6) slice(kb);
    if (RELPOS >= 6 && (kb > 0 || !FIRST)) {
      wg_wait<1>();
      arrive_one(B_EMPTY + 8 * ((kb + 5) % 6));
    }
  }
}

struct CtaId { int m, j; };
__device__ __forceinline__ CtaId map_cta(int bx) {
  if (MAPMODE == 0) return {bx & 15, bx >> 4};
  if (MAPMODE == 2) return {((bx >> 6) << 3) + ((bx >> 1) & 7), (((bx >> 4) & 3) << 1) + (bx & 1)};
  if (MAPMODE == 3) return {((bx >> 6) << 3) + (bx & 7), (((bx >> 4) & 3) << 1) + ((bx >> 3) & 1)};
  if (MAPMODE == 4) return {((bx >> 5) << 2) + (bx & 3), (((bx >> 4) & 1) << 2) + ((bx >> 2) & 3)};
  return {((bx >> 5) << 2) + ((bx >> 2) & 3), (((bx >> 4) & 1) << 2) + (bx & 3)};
}
__device__ __forceinline__ CtaId cta_id() {
  int bx; asm volatile("mov.u32 %0, %%ctaid.x;" : "=r"(bx));
  bx = __shfl_sync(0xffffffffu, bx, 0);
  return map_cta(bx);
}
__device__ __forceinline__ CtaId cta_id_lane() {
  int bx; asm volatile("mov.u32 %0, %%ctaid.x;" : "=r"(bx));
  return map_cta(bx);
}
struct Maps { CUtensorMap xraw3, x2, xt, xt64, xt8, yt, w1, w3, w2, x8, yt8; };

__global__ void __launch_bounds__(NTHR, 1) k_main(const __grid_constant__ Maps tm, const SsmParams sp, const __nv_bfloat16* __restrict__ dskip,
                                                   __nv_bfloat16* __restrict__ out) {
  extern __shared__ unsigned char smem_raw[];
  const int tid = threadIdx.x, wg = __shfl_sync(0xffffffffu, tid >> 7, 0);
  const int bx = blockIdx.x;
  const bool ffn = bx < NFFN;
  const int m = map_cta(bx).m, j = map_cta(bx).j;
  const int d0 = ffn ? bx * 4 : 512 + (bx - NFFN) * 16, npair = ffn ? 1 : 4;
  if (smem_u32(smem_raw) != S_X) return;
  if (wg == 2) {
    asm volatile("setmaxnreg.dec.sync.aligned.u32 24;");
    if (tid == 256) {
      mbar_init(B_RAW, 1);
      asm volatile("fence.mbarrier_init.release.cluster;" ::: "memory");
      if (ffn) { mbar_expect_tx(B_RAW, 18432); tma3d(S_LN, &tm.xraw3, 0, m * 128 + j * 16, 0, B_RAW); }
    } else if (tid >= 288 && tid < 336) {
      const int bi = tid - 288;
      const uint64_t tab = bi < 16 ? 0x88888800111111ull : (bi < 32 ? 0x8440180028011111ull : 0x111188814481440ull);
      const uint32_t c = (uint32_t)(tab >> (4 * (bi & 15))) & 15u;
      if (c) mbar_init(S_BAR + 8 * bi, (bi == 27 && ffn) ? 2 : c);
      asm volatile("fence.mbarrier_init.release.cluster;" ::: "memory");
    }
    bar_sync(0, NTHR);
    const int pw = (tid >> 5) & 3, lane = tid & 31;
    if (pw == 0) {
      if (lane == 0) {
        auto wload0 = [&](int kb0) {
          #pragma unroll 1
          for (int kb = kb0; kb < kb0 + 3; kb++) { mbar_expect_tx(B_FULL + 8 * kb, STG_BYTES); tma2d(S_RING + kb * STG_BYTES, &tm.w1, j * 576, kb * 96, B_FULL + 8 * kb); }
        };
        const unsigned int epoch = cur_epoch();
        if (ffn) {
          mbar_wait_long(B_RAW, 0);
          wload0(0);
        }
        if (ffn) mbar_wait_long(B_LN2, 0); else __nanosleep(2500);
        #pragma unroll 1
        for (int it = 0; it < 8192; it++) { unsigned int v; asm volatile("ld.acquire.gpu.global.u32 %0, [%1];" : "=r"(v) : "l"(&g_cnt_all) : "memory"); if (v == epoch * NFFN) break; }
        fence_async();
        #pragma unroll 1
        for (int it = 0; it < npair; it++) {
          if (it > 0) mbar_wait_long(B_CDONE, (it - 1) & 1);
          mbar_expect_tx(B_U, 16384);
          tma2d(S_U, &tm.xt, (d0 + it * 4) * 16, 0, B_U);
        }
        if (ffn) {
          #pragma unroll 1
          for (int w = 0; w < 2; w++) {
            mbar_wait_long(B_KDONE + 8 * w, 0);
            mbar_expect_tx(B_X + 8 * w, 3 * 16384);
            #pragma unroll 1
            for (int q = 0; q < 3; q++) tma3d(S_X + w * 65536 + q * 16384, &tm.xt64, 0, (w * 3 + q) * 16, m * 8, B_X + 8 * w);
          }
          mbar_wait_long(B_CDONE, 0);
          wload0(3);
          #pragma unroll 1
          for (int w = 0; w < 3; w++) {
            if (w > 0) mbar_wait_long(B_RDONE - 8 + 8 * w, 0);
            const uint32_t bar = B_X + (w ? 8 + 8 * w : 32);
            mbar_expect_tx(bar, 16384); tma3d(S_X + (w ? 4 * w - 1 : 8) * 16384, &tm.xt64, 0, w ? 80 + 16 * w : 128, m * 8, bar);
          }
          auto wpass = [&](const CUtensorMap* t, int c0, int c1, uint32_t par) {
            #pragma unroll
            for (int kb = 0; kb < 6; kb++) {
              mbar_spin(B_EMPTY + 8 * kb, par);
              mbar_expect_tx(B_FULL + 8 * kb, STG_BYTES);
              tma2d(S_RING + kb * STG_BYTES, t, c0, c1 + kb * 96, B_FULL + 8 * kb);
            }
          };
          const CUtensorMap* t = &tm.w3; int c0 = j * 576, c1 = 0;
          #pragma unroll 1
          for (int p = 1; p < 27; p++) {
            wpass(t, c0, c1, (p - 1) & 1);
            if (p < 17) { t = (p & 1) ? &tm.w1 : &tm.w3; c0 += (p & 1) * 64; }
            else { t = &tm.w2; c1 = j * 576; c0 = p == 17 ? 512 : ((j + p - 17) & 7) * 64; }
          }
        }
      }
      __syncwarp();
    } else {
      const int hw = pw - 1;
      if (tid == 352) { sts32(S_DSK + 196, atomicAdd(&g_ticket, 1) / NCTA + 1); mbar_arrive(B_EP); }
      if (tid == 320) { prefetch_tmap(&tm.xt); prefetch_tmap(&tm.w1); prefetch_tmap(&tm.xt64); prefetch_tmap(&tm.w3); }
      __syncwarp();
      if (hw == 0) {
        const unsigned int epoch = cur_epoch();
        if (ffn) { const uint32_t* dp = (const uint32_t*)dskip; sts32(S_DSK + lane * 4, __ldg(dp + j * 32 + (lane & 24) + ((lane >> 1) & 3) + (lane & 1) * 4)); if (lane < 4) sts32(S_DSK + 128 + lane * 4, __ldg(dp + 256 + j * 4 + lane)); }
        if (ffn && lane == 0) {
          mbar_wait_long(B_LN, 0);
          asm volatile("cp.async.bulk.global.shared::cta.bulk_group [%0], [%1], %2;" :: "l"(g_xt + (m * 128 + j * 16) * D_), "r"(S_LN + 18432), "r"(18432) : "memory");
          asm volatile("cp.async.bulk.commit_group;" ::: "memory");
          asm volatile("cp.async.bulk.wait_group 0;" ::: "memory");
          fence_async();
          red_add(&g_cnt_all);
          mbar_arrive(B_LN2);
        }
        __syncwarp();
        if (ffn) {
          #pragma unroll
          for (int i = 0; i < 7; i++) sts128(S_U - 3584 + i * 512 + lane * 16, 0, 0, 0, 0);
          fence_async_smem();
          __syncwarp();
          if (lane == 0) mbar_arrive(B_U);
        }
        mbar_wait_long(B_CDONE, 0);
        if (ffn) {
          uint4* za = g_acc + (m * 9 + j) * 1024 + lane;
          #pragma unroll 1
          for (int i = 0; i < 32; i++) za[i * 32] = make_uint4(0, 0, 0, 0);
          za = g_acc + (m * 9 + 8) * 1024 + j * 128 + lane;
          #pragma unroll 1
          for (int i = 0; i < 4; i++) za[i * 32] = make_uint4(0, 0, 0, 0);
        }
        __syncwarp();
        if (lane == 0) {
          mbar_wait_long(B_YDONE, 0);
          fence_gpu(); red_add(ffn ? &g_cnt_y : &g_cnt_ys);
          if (ffn) {
            prefetch_tmap(&tm.x2); prefetch_tmap(&tm.yt); prefetch_tmap(&tm.x8); prefetch_tmap(&tm.xt8); prefetch_tmap(&tm.yt8); prefetch_tmap(&tm.w2);
            flag_wait(&g_cnt_y, epoch * NFFN, 500); fence_async();
            mbar_arrive(B_GO);
            mbar_wait_long(B_PFREE, 0);
            mbar_expect_tx(B_H, 49152);
            __nanosleep(PACE); tma2d(S_X + 2 * 16384, &tm.x2, j * 64, m * 128, B_H); __nanosleep(PACE); tma3d(S_X + 3 * 16384, &tm.xt64, 0, j * 16, m * 8, B_H); __nanosleep(PACE);
            tma2d(S_X + 4 * 16384, &tm.yt, m * 128, j * 64, B_H); tma2d(S_X + 4 * 16384 + 8192, &tm.yt, m * 128 + 64, j * 64, B_H);
            #pragma unroll 1
            for (int k = 0; k < 3; k++) {
              mbar_wait_long(B_PUB + 8 * k, 0);
              fence_gpu();
              red_add(&g_cnt_acc[(m * 9 + (k ? (j + 2 * k) & 7 : 8)) * 8]);
              if (k < 2) red_add(&g_cnt_acc[(m * 9 + ((j + 2 * k + 1) & 7)) * 8]);
            }
            flag_wait(&g_cnt_acc[(m * 9 + j) * 8], epoch * 4, 50); fence_async();
            mbar_expect_tx(B_R, 16384); bulk_g2s(S_X + 6 * 16384, g_acc + (m * 9 + j) * 1024, 16384, B_R);
          }
        }
        __syncwarp();
      }
      if (ffn) {
        if (hw == 1 && lane == 0) {
          const CtaId id = cta_id_lane();
          mbar_wait_long(B_RAW, 0);
          #pragma unroll 1
          for (int p = 0; p < 27; p++) {
            if (p > PFLA) mbar_wait_long(B_FULL, (p - PFLA - 1) & 1);
            const int kb = (id.m - p * 6) & 15;
            if (kb < 6) {
              const CUtensorMap* t = p < 18 ? ((p & 1) ? &tm.w3 : &tm.w1) : &tm.w2;
              const int c0 = p < 18 ? id.j * 576 + (p >> 1) * 64 : (p == 18 ? 8 : ((id.j + p - 18) & 7)) * 64, c1 = (p < 18 ? 0 : id.j * 576) + kb * 96;
              asm volatile("cp.async.bulk.prefetch.tensor.2d.L2.global [%0, {%1, %2}];" :: "l"(t), "r"(c0), "r"(c1) : "memory");
            }
          }
        }
        __syncwarp();
        if (hw > 0) {
          mbar_wait_long(B_H, 0);
          {
            const uint32_t r7 = lane & 7, dq = (lane >> 4) * 2 + (r7 >> 2);
            const uint32_t na = S_X + 3 * 16384 + dq * 128 + ((((lane & 3) * 2 + ((lane >> 3) & 1)) ^ dq) << 4);
            const uint32_t ya = S_X + 4 * 16384 + ((lane >> 4) * 8 + r7) * 128 + ((((lane >> 3) & 1) ^ r7) << 4);
            const uint32_t xa = S_X + 2 * 16384 + (lane & 15) * 128 + (((lane >> 4) ^ r7) << 4);
            #pragma unroll 1
            for (int k = __shfl_sync(0xffffffffu, hw == 1 ? 0 : BSPLIT, 0), k1_ = __shfl_sync(0xffffffffu, hw == 1 ? BSPLIT : 32, 0); k < k1_; k++) {
              const uint32_t hf = (k >> 4) * 8192, i = (k >> 2) & 3, wp = k & 3;
              uint32_t x[4], n[4], y[4], k0, k1;
              ldsm_x4t((na ^ ((i & 1) * 64)) + hf + wp * 2048 + i * 512, n[0], n[1], n[2], n[3]);
              ldsm_x4t((ya ^ (wp * 32)) + hf + i * 2048, y[0], y[1], y[2], y[3]);
              ldsm_x4((xa ^ (i * 32)) + hf + wp * 2048, x[0], x[1], x[2], x[3]);
              lds64(S_DSK + i * 32 + (lane & 3) * 8, k0, k1);
              sts128(S_X + 7 * 16384 + k * 512 + lane * 16, add_bf16x2(x[0], add_bf16x2(y[0], mul_bf16x2(n[0], k0))), add_bf16x2(x[1], add_bf16x2(y[1], mul_bf16x2(n[1], k0))),
                     add_bf16x2(x[2], add_bf16x2(y[2], mul_bf16x2(n[2], k1))), add_bf16x2(x[3], add_bf16x2(y[3], mul_bf16x2(n[3], k1))));
            }
          }
          __syncwarp();
          if (lane == 0) {
            mbar_arrive(B_BASE);
            const CtaId id = cta_id_lane();
            const unsigned int epoch = cur_epoch();
            if (hw == 2) {
              flag_wait(&g_cnt_ys, epoch * (NCTA - NFFN), 300);
              flag_wait(&g_cnt_acc[(id.m * 9 + 8) * 8], epoch * 8, 300); fence_async();
              mbar_expect_tx(B_H8, 8192);
              tma2d(S_X + 8 * 16384, &tm.x8, 512 + id.j * 8, id.m * 128, B_H8); tma3d(S_X + 8 * 16384 + 2048, &tm.xt8, 0, 128 + id.j * 2, id.m * 8, B_H8);
              tma2d(S_X + 8 * 16384 + 4096, &tm.yt8, id.m * 128, 512 + id.j * 8, B_H8); tma2d(S_X + 8 * 16384 + 5120, &tm.yt8, id.m * 128 + 64, 512 + id.j * 8, B_H8);
              bulk_g2s(S_X + 8 * 16384 + 6144, g_acc + (id.m * 9 + 8) * 1024 + id.j * 128, 2048, B_H8);
            }
          }
          __syncwarp();
          if (hw == 2) {
            mbar_wait_long(B_H8, 0);
            const CtaId id = cta_id();
            const uint32_t h2 = (lane >> 2) & 1, hb = (lane >> 3) & 1;
            const uint32_t ta = (lane & 16) ? S_X + 8 * 16384 + 4096 + (lane & 7) * 128 + ((hb ^ (lane & 7)) << 4) : S_X + 8 * 16384 + 2048 + h2 * 128 + ((((lane & 3) * 2 + hb) ^ h2) << 4);
            const uint32_t k0 = lds32(S_DSK + 128 + (lane & 3) * 4);
            __nv_bfloat16* op = out + (id.m * 128 * D_ + 512 + id.j * 8) + (lane >> 2) * D_ + (lane & 3) * 2;
            #pragma unroll 1
            for (int k = 0; k < 8; k++, op += 16 * D_) {
              uint32_t x0, x1, n0, n1, y0, y1, v0, v1;
              asm volatile("ldmatrix.sync.aligned.m8n8.x2.shared.b16 {%0,%1}, [%2];" : "=r"(x0), "=r"(x1) : "r"(S_X + 8 * 16384 + k * 256 + (lane & 15) * 16) : "memory");
              ldsm_x4t((ta ^ ((k & 3) * 32)) + ((lane & 16) ? (k >> 2) * 1024 : k * 256), n0, n1, y0, y1);
              lds64(S_X + 8 * 16384 + 6144 + k * 256 + lane * 8, v0, v1);
              *(uint32_t*)op = add_bf16x2(add_bf16x2(x0, add_bf16x2(y0, mul_bf16x2(n0, k0))), v0);
              *(uint32_t*)(op + 8 * D_) = add_bf16x2(add_bf16x2(x1, add_bf16x2(y1, mul_bf16x2(n1, k0))), v1);
            }
          }
        }
      }
    }
  } else {
    asm volatile("setmaxnreg.inc.sync.aligned.u32 240;");
    const ModeRaw mr0 = load_mode(sp, d0 + wg * 2, tid & 127);
    bar_sync(0, NTHR);
    const int t128 = tid & 127, warp = t128 >> 5, lane = tid & 31;
        ssm_phase(sp, mr0, wg, d0, npair, ffn ? m * 128 + j * 16 : -1, t128);
    if (ffn) {
    uint32_t a[144];
    float accG[32], accU[32];
    Ring r{false, -1, 0};
    const uint32_t park = S_X + wg * 8192 + t128 * 16;
    auto nop = [](int) {};
    auto silu_slice = [&](int kb, int t) {
      if (kb >= 1 && kb <= 4) {
        const int i0 = (kb - 1) * 8;
        sts128(park + t * 16384 + (kb - 1) * 2048, pack_bf16(silu_f(accG[i0]), silu_f(accG[i0 + 1])), pack_bf16(silu_f(accG[i0 + 2]), silu_f(accG[i0 + 3])),
               pack_bf16(accG[i0 + 4], accG[i0 + 5]), pack_bf16(accG[i0 + 6], accG[i0 + 7]));
      }
    };
    auto mul_unit = [&](int i, int t, uint32_t& h0, uint32_t& h1, uint32_t& h2, uint32_t& h3) {
      uint32_t s0, s1, g2, g3; const int i0 = i * 8;
      lds128(park + t * 16384 + i * 2048, s0, s1, g2, g3);
      h0 = mul_bf16x2(s0, pack_bf16(accU[i0], accU[i0 + 1])); h1 = mul_bf16x2(s1, pack_bf16(accU[i0 + 2], accU[i0 + 3]));
      h2 = mul_bf16x2(pack_bf16(silu_f(bf_lo(g2)), silu_f(bf_hi(g2))), pack_bf16(accU[i0 + 4], accU[i0 + 5]));
      h3 = mul_bf16x2(pack_bf16(silu_f(bf_lo(g3)), silu_f(bf_hi(g3))), pack_bf16(accU[i0 + 6], accU[i0 + 7]));
    };
    {
      const uint32_t xrow = (lane >> 4) * 2 + ((lane >> 2) & 1);
      const uint32_t rbase = S_X + wg * 8192 + warp * 2048 + xrow * 128 + ((((lane & 3) * 2 + ((lane >> 3) & 1)) ^ xrow) << 4);
      auto ldx = [&](int kb) {
          if (kb == 0) mbar_wait(B_X, 0);
          if (kb == 2) mbar_wait(B_X + 8, 0);
          if (kb == 4) { mbar_wait(B_X + 16, 0); mbar_wait(B_X + 24, 0); }
          if (kb == 5) mbar_wait(B_X + 32, 0);
          #pragma unroll
          for (int kk = 0; kk < 6; kk++) {
            const int ks = kb * 6 + kk;
            ldsm_x4t((rbase ^ ((ks & 1) * 64)) + xslot(ks >> 2) * 16384 + (ks & 3) * 512, a[ks * 4 + 0], a[ks * 4 + 1], a[ks * 4 + 2], a[ks * 4 + 3]);
          }
        };
      run_pass<0, 0, 5, true>(accG, a, r, ldx, nop);
      ldx(5);
    }
    bar_sync(2 + wg, 128);
    auto reload = [&](int grp, int on) {
      #pragma unroll
      for (int i = 0; i < 6; i++) {
        const int q = grp * 6 + i;
        if (q < 32) asm volatile("{\n.reg .pred p;\nsetp.ne.b32 p, %5, 0;\n@p ld.shared.v4.b32 {%0,%1,%2,%3}, [%4];\n}\n"
                                 : "+r"(a[q * 4]), "+r"(a[q * 4 + 1]), "+r"(a[q * 4 + 2]), "+r"(a[q * 4 + 3]) : "r"(park + (q >> 2) * 16384 + (q & 3) * 2048), "r"(on) : "memory");
      }
    };
    #pragma unroll 1
    for (int t = 0; t < 9; t++) {
      run_pass<0, 5, 6>(accG, a, r, nop, nop);
      run_pass<1>(accU, a, r, nop, [&](int kb) { silu_slice(kb, t); if (kb >= 2) reload(kb - 2, t == 8); });
      run_pass<0, 0, 5>(accG, a, r, nop, [&](int kb) {
        if (kb <= 1) reload(4 + kb, t == 8);
        if (kb >= 1) {
          uint32_t h0, h1, h2, h3; mul_unit(kb - 1, t, h0, h1, h2, h3);
          sts128(park + t * 16384 + (kb - 1) * 2048, h0, h1, h2, h3);
          asm volatile("{\n.reg .pred p;\nsetp.ne.b32 p, %8, 0;\n@p mov.b32 %0, %4;\n@p mov.b32 %1, %5;\n@p mov.b32 %2, %6;\n@p mov.b32 %3, %7;\n}\n"
                       : "+r"(a[124 + kb * 4]), "+r"(a[125 + kb * 4]), "+r"(a[126 + kb * 4]), "+r"(a[127 + kb * 4]) : "r"(h0), "r"(h1), "r"(h2), "r"(h3), "r"((int)(t == 8)));
        } });
      r.ts = -1;
    }
    fence_async_smem(); __syncwarp(); arrive_one(B_PFREE);
    const uint32_t tag = opaque(cur_epoch() & 1);
    const CtaId id2 = cta_id(); const int m = id2.m, j = id2.j;
    const uint32_t pk = park - S_X;
    auto store_vec = [&](const float* acc, int t, int i, bool may0) {
      uint32_t w0 = pack_bf16(acc[i * 8], acc[i * 8 + 1]), w1 = pack_bf16(acc[i * 8 + 2], acc[i * 8 + 3]), w2 = pack_bf16(acc[i * 8 + 4], acc[i * 8 + 5]), w3 = pack_bf16(acc[i * 8 + 6], acc[i * 8 + 7]);
      if (may0 && __builtin_expect(t == 0, 0)) {
        if (i == 0) mbar_wait(B_GO, 0);
        const uint32_t pq = opaque(pk);
        char* dst = (char*)g_acc + (size_t)(m * 9 + 8) * 16384 + i * 4096 + (((pq >> 1) & 1023) | ((pq >> 3) & 1024));
        asm volatile("red.relaxed.gpu.global.add.noftz.v2.bf16x2 [%0], {%1,%2};" :: "l"(dst), "r"(w0), "r"(w1) : "memory");
        asm volatile("red.relaxed.gpu.global.add.noftz.v2.bf16x2 [%0], {%1,%2};" :: "l"(dst + 2048), "r"(w2), "r"(w3) : "memory");
      } else {
        const int blk = (j + t) & 7;
        const char* base = t >= 5 ? (const char*)g_part + (size_t)((m * 8 + blk) * 3 + t - 5) * 16384 : (const char*)g_acc + (size_t)(m * 9 + blk) * 16384;
        asm volatile("{\n.reg .pred p;\n.reg .b32 a, b, c, d;\nsetp.ge.s32 p, %6, 5;\n"
                     "lop3.b32 a, %1, -2, %5, 0xEA;\nlop3.b32 b, %2, -2, %5, 0xEA;\nlop3.b32 c, %3, -2, %5, 0xEA;\nlop3.b32 d, %4, -2, %5, 0xEA;\n"
                     "@p st.relaxed.gpu.global.v4.b32 [%0], {a,b,c,d};\n@!p red.relaxed.gpu.global.add.noftz.v4.bf16x2 [%0], {%1,%2,%3,%4};\n}\n"
                     :: "l"(base + i * 2048 + pk), "r"(w0), "r"(w1), "r"(w2), "r"(w3), "r"(tag), "r"(t) : "memory");
        if (i == 3) { __syncwarp(); asm volatile("{\n.reg .pred p, q;\nelect.sync _|p, 0xffffffff;\nsetp.ne.and.b32 q, %1, 0, p;\n@q mbarrier.arrive.shared::cta.b64 _, [%0];\n}\n" :: "r"(B_PUB + 8 * (t >> 1)), "r"((int)(t < 5 && t != 2)) : "memory"); }
      }
    };
    auto own_part = [&](int s) { return (const char*)g_part + (size_t)((m * 8 + j) * 3 + s - 5) * 16384 + pk; };
    auto fetch = [&](int s) {
      const char* src = own_part(s);
      #pragma unroll
      for (int i = 0; i < 4; i++) cp_async16(park + (s == 7 ? 5 : (s & 1)) * 16384 + i * 2048, src + i * 2048);
      cp_commit();
    };
    uint32_t missing = 0;
    auto final_vec = [&](int i) {
      uint32_t v[4], f[4], b[4];
      lds128(park + 16384 + i * 2048, v[0], v[1], v[2], v[3]);
      lds128(park + 6 * 16384 + i * 2048, f[0], f[1], f[2], f[3]); lds128(park + 7 * 16384 + i * 2048, b[0], b[1], b[2], b[3]);
      if (tag_bad(v[0], v[1], v[2], v[3], tag)) missing |= 1u << i;
      else sts128(park + 6 * 16384 + i * 2048, add_bf16x2(f[0], v[0]), add_bf16x2(f[1], v[1]), add_bf16x2(f[2], v[2]), add_bf16x2(f[3], v[3]));
      #pragma unroll
      for (int e = 0; e < 4; e++) { accU[i * 8 + 2 * e] = bf_lo(b[e]); accU[i * 8 + 2 * e + 1] = bf_hi(b[e]); }
    };
    #pragma unroll 1
    for (int u = 1; u < 7; u += 2) {
      run_pass<0, 5, 6>(accG, a, r, nop, nop);
      run_pass<1>(accU, a, r, nop, [&](int kb) { if (kb >= 1 && kb <= 4) store_vec(accG, u - 1, kb - 1, true); });
      run_pass<0, 0, 5>(accG, a, r, nop, [&](int kb) { if (kb >= 1) store_vec(accU, u, kb - 1, false); });
    }
    run_pass<0, 5, 6>(accG, a, r, nop, nop);
    run_pass<1>(accU, a, r, nop, [&](int kb) { if (kb >= 1 && kb <= 4) store_vec(accG, 6, kb - 1, false); if (kb == 5) fetch(5); });
    run_pass<0, 0, 5>(accG, a, r, nop, [&](int kb) {
      if (kb == 0) { wg_wait<0>(); store_vec(accU, 7, 0, false); store_vec(accU, 7, 1, false); }
      if (kb == 1) { store_vec(accU, 7, 2, false); store_vec(accU, 7, 3, false); fetch(6); }
      if (kb == 2) { mbar_wait(B_BASE, 0); mbar_wait(B_R, 0); if (SENDV == 2) cp_wait<0>(); else cp_wait<1>(); }
      if (kb >= 2) final_vec(kb - 2);
      if (kb == 4) fetch(7); });
    {
      run_pass<0, 5, 6, false, true>(accG, a, r, nop, [&](int) { final_vec(3); });
      cp_wait<0>();
      #pragma unroll
      for (int i = 0; i < 4; i++) {
        uint32_t v[4], w[4], f[4]; lds128(park + i * 2048, w[0], w[1], w[2], w[3]); lds128(park + 5 * 16384 + i * 2048, v[0], v[1], v[2], v[3]); lds128(park + 6 * 16384 + i * 2048, f[0], f[1], f[2], f[3]);
        if (tag_bad(w[0], w[1], w[2], w[3], tag)) { missing |= 16u << i; w[0] = w[1] = w[2] = w[3] = 0; }
        if (tag_bad(v[0], v[1], v[2], v[3], tag)) { missing |= 256u << i; v[0] = v[1] = v[2] = v[3] = 0; }
        add_vec(accU + i * 8, add_bf16x2(f[0], add_bf16x2(v[0], w[0])), add_bf16x2(f[1], add_bf16x2(v[1], w[1])), add_bf16x2(f[2], add_bf16x2(v[2], w[2])), add_bf16x2(f[3], add_bf16x2(v[3], w[3])));
      }
      #pragma unroll 1
      for (int it = 0; missing && it < 4096; it++) {
        const int s = (__ffs(missing) - 1) >> 2;
        const uint4* src = (const uint4*)own_part(5 + s);
        uint32_t v[16];
        #pragma unroll
        for (int i = 0; i < 4; i++) ld_relaxed_v4(src + i * 128, v[i * 4], v[i * 4 + 1], v[i * 4 + 2], v[i * 4 + 3]);
        #pragma unroll
        for (int i = 0; i < 4; i++)
          if ((missing >> (4 * s + i) & 1) && !tag_bad(v[i * 4], v[i * 4 + 1], v[i * 4 + 2], v[i * 4 + 3], tag)) { add_vec(accU + i * 8, v[i * 4], v[i * 4 + 1], v[i * 4 + 2], v[i * 4 + 3]); missing &= ~(1u << (4 * s + i)); }
      }
      __syncwarp();
      wg_wait<0>();
      #pragma unroll
      for (int i = 0; i < 32; i++) accU[i] += accG[i];
      const uint32_t pq = opaque(pk); const int lane = (pq >> 4) & 31, warp = (pq >> 9) & 3, wg = pq >> 13;
      const uint32_t stg = S_X + 4 * 16384 + wg * 8192 + warp * 2048;
      #pragma unroll
      for (int i = 0; i < 4; i++) {
        const int row = (lane & 7) + ((lane >> 3) & 1) * 8, chunk = 2 * i + (lane >> 4);
        asm volatile("stmatrix.sync.aligned.m8n8.x4.shared.b16 [%0], {%1,%2,%3,%4};" :: "r"(stg + row * 128 + ((chunk ^ (row & 7)) << 4)),
                     "r"(pack_bf16(accU[i * 8], accU[i * 8 + 1])), "r"(pack_bf16(accU[i * 8 + 2], accU[i * 8 + 3])), "r"(pack_bf16(accU[i * 8 + 4], accU[i * 8 + 5])), "r"(pack_bf16(accU[i * 8 + 6], accU[i * 8 + 7])) : "memory");
      }
      __syncwarp();
      #pragma unroll
      for (int i = 0; i < 4; i++) {
        const int row = i * 4 + (lane >> 3), chunk = lane & 7;
        uint32_t o0, o1, o2, o3; lds128(stg + row * 128 + ((chunk ^ (row & 7)) << 4), o0, o1, o2, o3);
        *(uint4*)(out + (m * 128 + wg * 64 + warp * 16 + row) * D_ + j * 64 + chunk * 8) = make_uint4(o0, o1, o2, o3);
      }
    }
    }
  }
}

typedef CUresult (*EncFn)(CUtensorMap*, CUtensorMapDataType, cuuint32_t, void*, const cuuint64_t*, const cuuint64_t*, const cuuint32_t*, const cuuint32_t*, CUtensorMapInterleave, CUtensorMapSwizzle, CUtensorMapL2promotion, CUtensorMapFloatOOBfill);
static void enc(EncFn f, CUtensorMap* tm, const void* base, int rank, uint64_t d0, uint64_t d1, uint64_t d2, uint64_t s1, uint64_t s2, uint32_t b0, uint32_t b1, uint32_t b2, CUtensorMapSwizzle sw) {
  cuuint64_t dims[3] = {d0, d1, d2}; cuuint64_t strides[2] = {s1, s2}; cuuint32_t box[3] = {b0, b1, b2}; cuuint32_t es[3] = {1, 1, 1};
  CUresult r = f(tm, CU_TENSOR_MAP_DATA_TYPE_BFLOAT16, rank, (void*)base, dims, strides, box, es, CU_TENSOR_MAP_INTERLEAVE_NONE, sw, CU_TENSOR_MAP_L2_PROMOTION_L2_128B, CU_TENSOR_MAP_FLOAT_OOB_FILL_NONE);
  if (r != CUDA_SUCCESS) fprintf(stderr, "tensor map encode failed %d\n", (int)r);
}

extern "C" void kernel_launch(void* const* d_in, const int* in_sizes, int n_in, void* d_out, int out_size) {
  static bool init = false;
  static Maps tm;
  if (!init) {
    void* fn = nullptr; cudaDriverEntryPointQueryResult st;
    cudaGetDriverEntryPoint("cuTensorMapEncodeTiled", &fn, cudaEnableDefault, &st);
    EncFn f = (EncFn)fn;
    void *xt, *yt; cudaGetSymbolAddress(&xt, g_xt); cudaGetSymbolAddress(&yt, g_yt);
    const CUtensorMapSwizzle S128 = CU_TENSOR_MAP_SWIZZLE_128B;
    enc(f, &tm.xraw3, d_in[0], 3, 64, L_, 9, D_ * 2, 128, 64, 16, 9, S128);
    enc(f, &tm.x2, d_in[0], 2, D_, L_, 1, D_ * 2, 0, 64, 128, 1, S128);
    enc(f, &tm.xt64, xt, 3, 64, D_ / 4, 128, 128, 32 * D_, 64, 16, 8, S128);
    enc(f, &tm.xt8, xt, 3, 64, D_ / 4, 128, 128, 32 * D_, 64, 2, 8, S128);
    enc(f, &tm.xt, xt, 2, 16 * D_, 128, 1, 32 * D_, 0, 64, 128, 1, S128);
    enc(f, &tm.yt, yt, 2, L_, D_, 1, L_ * 2, 0, 64, 64, 1, S128);
    enc(f, &tm.w1, d_in[10], 2, F_, D_, 1, F_ * 2, 0, 64, 96, 1, S128);
    enc(f, &tm.w3, d_in[11], 2, F_, D_, 1, F_ * 2, 0, 64, 96, 1, S128);
    enc(f, &tm.w2, d_in[12], 2, D_, F_, 1, D_ * 2, 0, 64, 96, 1, S128);
    enc(f, &tm.x8, d_in[0], 2, D_, L_, 1, D_ * 2, 0, 8, 128, 1, CU_TENSOR_MAP_SWIZZLE_NONE);
    enc(f, &tm.yt8, yt, 2, L_, D_, 1, L_ * 2, 0, 64, 8, 1, S128);
    cudaFuncSetAttribute(k_main, cudaFuncAttributeMaxDynamicSharedMemorySize, SMEM_BYTES);
    init = true;
  }
  SsmParams sp{(const __nv_bfloat16*)d_in[1], (const __nv_bfloat16*)d_in[2], (const __nv_bfloat16*)d_in[3], (const __nv_bfloat16*)d_in[4],
               (const __nv_bfloat16*)d_in[5], (const __nv_bfloat16*)d_in[6], (const __nv_bfloat16*)d_in[7]};
  k_main<<<NCTA, NTHR, SMEM_BYTES>>>(tm, sp, (const __nv_bfloat16*)d_in[8], (__nv_bfloat16*)d_out);
}
```

```cpp
#include <cuda_runtime.h>
#include <cuda.h>
#include <cuda_bf16.h>
#include <stdint.h>
#include <stdio.h>

__device__ __forceinline__ void wgmma_rs_n64_t1(float* d, uint32_t a0, uint32_t a1, uint32_t a2, uint32_t a3, uint64_t descB, int scaleD) {
  asm volatile("{\n.reg .pred p;\nsetp.ne.b32 p, %37, 0;\n"
    "wgmma.mma_async.sync.aligned.m64n64k16.f32.bf16.bf16 {%0,%1,%2,%3,%4,%5,%6,%7,%8,%9,%10,%11,%12,%13,%14,%15,%16,%17,%18,%19,%20,%21,%22,%23,%24,%25,%26,%27,%28,%29,%30,%31}, {%32,%33,%34,%35}, %36, p, 1, 1, 1;\n}\n"
    : "+f"(d[0]), "+f"(d[1]), "+f"(d[2]), "+f"(d[3]), "+f"(d[4]), "+f"(d[5]), "+f"(d[6]), "+f"(d[7]), "+f"(d[8]), "+f"(d[9]), "+f"(d[10]), "+f"(d[11]), "+f"(d[12]), "+f"(d[13]), "+f"(d[14]), "+f"(d[15]), "+f"(d[16]), "+f"(d[17]), "+f"(d[18]), "+f"(d[19]), "+f"(d[20]), "+f"(d[21]), "+f"(d[22]), "+f"(d[23]), "+f"(d[24]), "+f"(d[25]), "+f"(d[26]), "+f"(d[27]), "+f"(d[28]), "+f"(d[29]), "+f"(d[30]), "+f"(d[31])
    : "r"(a0), "r"(a1), "r"(a2), "r"(a3), "l"(descB), "r"(scaleD));
}
__device__ __forceinline__ void wgmma_ss_n48_t0(float* d, uint64_t descA, uint64_t descB, int scaleD) {
  asm volatile("{\n.reg .pred p;\nsetp.ne.b32 p, %26, 0;\n"
    "wgmma.mma_async.sync.aligned.m64n48k16.f32.bf16.bf16 {%0,%1,%2,%3,%4,%5,%6,%7,%8,%9,%10,%11,%12,%13,%14,%15,%16,%17,%18,%19,%20,%21,%22,%23}, %24, %25, p, 1, 1, 0, 0;\n}\n"
    : "+f"(d[0]), "+f"(d[1]), "+f"(d[2]), "+f"(d[3]), "+f"(d[4]), "+f"(d[5]), "+f"(d[6]), "+f"(d[7]), "+f"(d[8]), "+f"(d[9]), "+f"(d[10]), "+f"(d[11]), "+f"(d[12]), "+f"(d[13]), "+f"(d[14]), "+f"(d[15]), "+f"(d[16]), "+f"(d[17]), "+f"(d[18]), "+f"(d[19]), "+f"(d[20]), "+f"(d[21]), "+f"(d[22]), "+f"(d[23])
    : "l"(descA), "l"(descB), "r"(scaleD));
}
__device__ __forceinline__ void wgmma_rs_n32_t0(float* d, uint32_t a0, uint32_t a1, uint32_t a2, uint32_t a3, uint64_t descB, int scaleD) {
  asm volatile("{\n.reg .pred p;\nsetp.ne.b32 p, %21, 0;\n"
    "wgmma.mma_async.sync.aligned.m64n32k16.f32.bf16.bf16 {%0,%1,%2,%3,%4,%5,%6,%7,%8,%9,%10,%11,%12,%13,%14,%15}, {%16,%17,%18,%19}, %20, p, 1, 1, 0;\n}\n"
    : "+f"(d[0]), "+f"(d[1]), "+f"(d[2]), "+f"(d[3]), "+f"(d[4]), "+f"(d[5]), "+f"(d[6]), "+f"(d[7]), "+f"(d[8]), "+f"(d[9]), "+f"(d[10]), "+f"(d[11]), "+f"(d[12]), "+f"(d[13]), "+f"(d[14]), "+f"(d[15])
    : "r"(a0), "r"(a1), "r"(a2), "r"(a3), "l"(descB), "r"(scaleD));
}


constexpr int SLPOS = 2;
constexpr int PFLA = 6;
constexpr int PACE = 300;
constexpr int BSPLIT = 22;
constexpr int L_ = 2048, D_ = 576, F_ = 4608;
constexpr int NFFN = 128, NCTA = 132, NTHR = 384;
constexpr int STG_BYTES = 12288;
constexpr uint32_t S_X = 1024;
constexpr uint32_t S_RING = S_X + 147456;
constexpr uint32_t S_MISC = S_RING + 6 * STG_BYTES;
constexpr uint32_t S_BAR = S_MISC + 8320, S_DSK = S_BAR + 512, S_DUMMY = S_DSK + 256;
constexpr int SMEM_BYTES = S_DUMMY + 256 - 1024;
constexpr uint32_t B_FULL = S_BAR, B_EMPTY = S_BAR + 64, B_X = S_BAR + 128  , B_PFREE = S_BAR + 176, B_BASE = S_BAR + 184  ,
                   B_RAW = S_BAR + 200, B_LN = S_BAR + 208, B_U = S_BAR + 216  , B_KDONE = S_BAR + 232  , B_CDONE = S_BAR + 248  ,
                   B_RDONE = S_BAR + 264  , B_H = S_BAR + 280, B_YDONE = S_BAR + 288, B_PP = S_BAR + 296  , B_GO = S_BAR + 312, B_PUB = S_BAR + 320  , B_R = S_BAR + 344, B_H8 = S_BAR + 352, B_EP = S_BAR + 360, B_LN2 = S_BAR + 368;
constexpr uint32_t S_LN = S_RING + 3 * STG_BYTES;
constexpr uint32_t S_U = S_LN + 20480;
__device__ __forceinline__ uint32_t s_w_of(int ch) { return ch < 2 ? S_LN + ch * 8256 : (ch == 2 ? S_X + 8 * 16384 : S_MISC); }
__host__ __device__ constexpr int xslot(int kb) { return kb < 3 ? kb : (kb < 6 ? kb + 1 : (kb == 6 ? 3 : kb)); }

__device__ __nv_bfloat16 g_xt[D_ * L_];
__device__ __nv_bfloat16 g_yt[D_ * L_];
__device__ uint4 g_part[16 * 8 * 3 * 1024];
__device__ uint4 g_acc[16 * 9 * 1024];
__device__ unsigned int g_cnt_acc[16 * 9 * 8];
__device__ unsigned int g_ticket, g_cnt_all, g_cnt_y, g_cnt_ys;

__device__ __forceinline__ uint32_t smem_u32(const void* p) { return (uint32_t)__cvta_generic_to_shared(p); }
__device__ __forceinline__ void mbar_init(uint32_t bar, uint32_t cnt) { asm volatile("mbarrier.init.shared::cta.b64 [%0], %1;" :: "r"(bar), "r"(cnt)); }
__device__ __forceinline__ void mbar_expect_tx(uint32_t bar, uint32_t bytes) { asm volatile("mbarrier.arrive.expect_tx.shared::cta.b64 _, [%0], %1;" :: "r"(bar), "r"(bytes) : "memory"); }
__device__ __forceinline__ void mbar_arrive(uint32_t bar) { asm volatile("mbarrier.arrive.shared::cta.b64 _, [%0];" :: "r"(bar) : "memory"); }
__device__ __forceinline__ bool mbar_try_wait(uint32_t bar, uint32_t parity) {
  uint32_t ok;
  asm volatile("{\n.reg .pred p;\nmbarrier.try_wait.parity.shared::cta.b64 p, [%1], %2;\nselp.u32 %0, 1, 0, p;\n}\n" : "=r"(ok) : "r"(bar), "r"(parity) : "memory");
  return ok;
}
__device__ __forceinline__ void mbar_wait(uint32_t bar, uint32_t parity) {
  asm volatile("{\n.reg .pred p;\n.reg .u32 c;\nmov.u32 c, 0;\n"
               "WAIT_LOOP:\nmbarrier.try_wait.parity.shared::cta.b64 p, [%0], %1;\nadd.u32 c, c, 1;\n@!p setp.gt.u32 p, c, 8192;\n@!p bra WAIT_LOOP;\n}\n" :: "r"(bar), "r"(parity) : "memory");
}
__device__ __forceinline__ void mbar_wait_long(uint32_t bar, uint32_t parity) {
  asm volatile("{\n.reg .pred p;\n.reg .u32 t0, t1;\nmov.u32 t0, %%clock;\n"
               "WAIT_LOOP:\nmbarrier.try_wait.parity.shared::cta.b64 p, [%0], %1;\nmov.u32 t1, %%clock;\nsub.u32 t1, t1, t0;\n@!p setp.gt.u32 p, t1, 0x800000;\n@!p bra WAIT_LOOP;\n}\n" :: "r"(bar), "r"(parity) : "memory");
}
__device__ __forceinline__ void mbar_spin(uint32_t bar, uint32_t parity) {
  asm volatile("{\n.reg .pred p;\n.reg .u32 c;\nmov.u32 c, 0;\n"
               "SPIN_LOOP:\nmbarrier.test_wait.parity.shared::cta.b64 p, [%0], %1;\nadd.u32 c, c, 1;\n@!p setp.gt.u32 p, c, 0x100000;\n@!p bra SPIN_LOOP;\n}\n" :: "r"(bar), "r"(parity) : "memory");
}
__device__ __forceinline__ void flag_wait(const unsigned int* f, unsigned int val, unsigned int ns) {
  unsigned int v;
  #pragma unroll 1
  for (int it = 0; it < 16384; it++) {
    asm volatile("ld.relaxed.gpu.global.u32 %0, [%1];" : "=r"(v) : "l"(f) : "memory");
    if (v == val) break;
    __nanosleep(ns);
  }
  asm volatile("ld.acquire.gpu.global.u32 %0, [%1];" : "=r"(v) : "l"(f) : "memory");
}
__device__ __forceinline__ void red_add(unsigned int* p) { asm volatile("red.relaxed.gpu.global.add.u32 [%0], 1;" :: "l"(p) : "memory"); }
__device__ __forceinline__ void fence_gpu() { asm volatile("fence.acq_rel.gpu;" ::: "memory"); }
__device__ __forceinline__ void fence_async() { asm volatile("fence.proxy.async.global;" ::: "memory"); }
__device__ __forceinline__ void fence_async_smem() { asm volatile("fence.proxy.async.shared::cta;" ::: "memory"); }
__device__ __forceinline__ unsigned int cur_epoch() { mbar_wait(B_EP, 0); unsigned int v; asm volatile("ld.shared.b32 %0, [%1];" : "=r"(v) : "r"(S_DSK + 196) : "memory"); return v; }
__device__ __forceinline__ void tma2d(uint32_t dst, const CUtensorMap* tm, int c0, int c1, uint32_t bar) {
  asm volatile("cp.async.bulk.tensor.2d.shared::cluster.global.mbarrier::complete_tx::bytes [%0], [%1, {%3, %4}], [%2];" :: "r"(dst), "l"(tm), "r"(bar), "r"(c0), "r"(c1) : "memory");
}
__device__ __forceinline__ void tma3d(uint32_t dst, const CUtensorMap* tm, int c0, int c1, int c2, uint32_t bar) {
  asm volatile("cp.async.bulk.tensor.3d.shared::cluster.global.mbarrier::complete_tx::bytes [%0], [%1, {%3, %4, %5}], [%2];" :: "r"(dst), "l"(tm), "r"(bar), "r"(c0), "r"(c1), "r"(c2) : "memory");
}
__device__ __forceinline__ void bulk_g2s(uint32_t dst, const void* src, uint32_t bytes, uint32_t bar) {
  asm volatile("cp.async.bulk.shared::cluster.global.mbarrier::complete_tx::bytes [%0], [%1], %2, [%3];" :: "r"(dst), "l"(src), "r"(bytes), "r"(bar) : "memory");
}
__device__ __forceinline__ void prefetch_tmap(const CUtensorMap* tm) { asm volatile("prefetch.tensormap [%0];" :: "l"(tm) : "memory"); }
__device__ __forceinline__ void wg_fence() { asm volatile("wgmma.fence.sync.aligned;" ::: "memory"); }
__device__ __forceinline__ void wg_commit() { asm volatile("wgmma.commit_group.sync.aligned;" ::: "memory"); }
template <int N> __device__ __forceinline__ void wg_wait() { asm volatile("wgmma.wait_group.sync.aligned %0;" :: "n"(N) : "memory"); }
__device__ __forceinline__ void bar_sync(int id, int n) { asm volatile("bar.sync %0, %1;" :: "r"(id), "r"(n) : "memory"); }
__device__ __forceinline__ uint32_t pack_bf16(float lo, float hi) { uint32_t r; asm("cvt.rn.bf16x2.f32 %0, %1, %2;" : "=r"(r) : "f"(hi), "f"(lo)); return r; }
__device__ __forceinline__ float bf_lo(uint32_t v) { return __uint_as_float(v << 16); }
__device__ __forceinline__ float bf_hi(uint32_t v) { return __uint_as_float(v & 0xFFFF0000u); }
__device__ __forceinline__ float bf_round(float v) { return bf_lo(pack_bf16(v, v)); }
__device__ __forceinline__ uint32_t mul_bf16x2(uint32_t a, uint32_t b) { uint32_t r; asm("mul.rn.bf16x2 %0, %1, %2;" : "=r"(r) : "r"(a), "r"(b)); return r; }
__device__ __forceinline__ uint32_t add_bf16x2(uint32_t a, uint32_t b) { uint32_t r; asm("add.rn.bf16x2 %0, %1, %2;" : "=r"(r) : "r"(a), "r"(b)); return r; }
__device__ __forceinline__ uint32_t sub_bf16x2(uint32_t a, uint32_t b) { uint32_t r; asm("sub.rn.bf16x2 %0, %1, %2;" : "=r"(r) : "r"(a), "r"(b)); return r; }
__device__ __forceinline__ void ldsm_x4(uint32_t addr, uint32_t& r0, uint32_t& r1, uint32_t& r2, uint32_t& r3) {
  asm volatile("ldmatrix.sync.aligned.m8n8.x4.shared.b16 {%0,%1,%2,%3}, [%4];" : "=r"(r0), "=r"(r1), "=r"(r2), "=r"(r3) : "r"(addr) : "memory");
}
__device__ __forceinline__ void ldsm_x4t(uint32_t addr, uint32_t& r0, uint32_t& r1, uint32_t& r2, uint32_t& r3) {
  asm volatile("ldmatrix.sync.aligned.m8n8.x4.trans.shared.b16 {%0,%1,%2,%3}, [%4];" : "=r"(r0), "=r"(r1), "=r"(r2), "=r"(r3) : "r"(addr) : "memory");
}
__device__ __forceinline__ float silu_f(float g) {
  const float h = 0.5f * g; float th; asm("tanh.approx.f32 %0, %1;" : "=f"(th) : "f"(h));
  return fmaf(h, th, h);
}
__device__ __forceinline__ void sts128(uint32_t addr, uint32_t a, uint32_t b, uint32_t c, uint32_t d) { asm volatile("st.shared.v4.b32 [%0], {%1,%2,%3,%4};" :: "r"(addr), "r"(a), "r"(b), "r"(c), "r"(d) : "memory"); }
__device__ __forceinline__ void sts64(uint32_t addr, uint32_t a, uint32_t b) { asm volatile("st.shared.v2.b32 [%0], {%1,%2};" :: "r"(addr), "r"(a), "r"(b) : "memory"); }
__device__ __forceinline__ void sts32(uint32_t addr, uint32_t a) { asm volatile("st.shared.b32 [%0], %1;" :: "r"(addr), "r"(a) : "memory"); }
__device__ __forceinline__ void lds128(uint32_t addr, uint32_t& a, uint32_t& b, uint32_t& c, uint32_t& d) { asm volatile("ld.shared.v4.b32 {%0,%1,%2,%3}, [%4];" : "=r"(a), "=r"(b), "=r"(c), "=r"(d) : "r"(addr) : "memory"); }
__device__ __forceinline__ void lds64(uint32_t addr, uint32_t& a, uint32_t& b) { asm volatile("ld.shared.v2.b32 {%0,%1}, [%2];" : "=r"(a), "=r"(b) : "r"(addr) : "memory"); }
__device__ __forceinline__ uint32_t lds32(uint32_t addr) { uint32_t a; asm volatile("ld.shared.b32 %0, [%1];" : "=r"(a) : "r"(addr) : "memory"); return a; }
__device__ __forceinline__ float ldsf(uint32_t addr) { float a; asm volatile("ld.shared.f32 %0, [%1];" : "=f"(a) : "r"(addr) : "memory"); return a; }
__device__ __forceinline__ uint32_t opaque(uint32_t v) { uint32_t r; asm volatile("mov.b32 %0, %1;" : "=r"(r) : "r"(v)); return r; }
__device__ __forceinline__ void cp_async16(uint32_t dst, const void* src) { asm volatile("cp.async.cg.shared.global [%0], [%1], 16;" :: "r"(dst), "l"(src) : "memory"); }
__device__ __forceinline__ void cp_commit() { asm volatile("cp.async.commit_group;" ::: "memory"); }
template <int N> __device__ __forceinline__ void cp_wait() { asm volatile("cp.async.wait_group %0;" :: "n"(N) : "memory"); }
__device__ __forceinline__ void ld_relaxed_v4(const uint4* p, uint32_t& a, uint32_t& b, uint32_t& c, uint32_t& d) {
  asm volatile("ld.relaxed.gpu.global.v4.b32 {%0,%1,%2,%3}, [%4];" : "=r"(a), "=r"(b), "=r"(c), "=r"(d) : "l"(p) : "memory");
}
__device__ __forceinline__ bool tag_bad(uint32_t a, uint32_t b, uint32_t c, uint32_t d, uint32_t tag) { return (((a ^ tag) | (b ^ tag) | (c ^ tag) | (d ^ tag)) & 1u) != 0; }
__device__ __forceinline__ void add_vec(float* f, uint32_t v0, uint32_t v1, uint32_t v2, uint32_t v3) {
  f[0] += bf_lo(v0); f[1] += bf_hi(v0); f[2] += bf_lo(v1); f[3] += bf_hi(v1); f[4] += bf_lo(v2); f[5] += bf_hi(v2); f[6] += bf_lo(v3); f[7] += bf_hi(v3);
}

struct cplx { float re, im; };
__device__ __forceinline__ cplx cmul(cplx a, cplx b) { return {fmaf(a.re, b.re, -a.im * b.im), fmaf(a.re, b.im, a.im * b.re)}; }
__device__ __forceinline__ cplx cexp_f(float ar, float ai) {
  float mag; asm("ex2.approx.f32 %0, %1;" : "=f"(mag) : "f"(ar * 1.4426950408889634f));
  const float k = rintf(ai * 0.15915494309189535f);
  float r = fmaf(ai, 0.15915494309189535f, -k);
  r = fmaf(ai, 6.4206383e-9f, r);
  r *= 6.283185307179586f;
  float sn, cs; asm("sin.approx.f32 %0, %1;" : "=f"(sn) : "f"(r)); asm("cos.approx.f32 %0, %1;" : "=f"(cs) : "f"(r));
  return {mag * cs, mag * sn};
}
__device__ __forceinline__ float bf2f(__nv_bfloat16 v) { return __bfloat162float(v); }

constexpr int KG_B = 32768, KG_TAB = 2688;

struct SsmParams { const __nv_bfloat16 *are, *aim, *bre, *bim, *cre, *cim, *logdt; };
struct ModeRaw { uint32_t are, aim, bre, bim, cre, cim; __nv_bfloat16 ldt; };
__device__ __forceinline__ ModeRaw load_mode(const SsmParams& p, int d, int t128) {
  const int o = d * 64 + t128;
  auto ld = [&](const __nv_bfloat16* b) { return __ldg((const uint32_t*)b + o); };
  return {ld(p.are), ld(p.aim), ld(p.bre), ld(p.bim), ld(p.cre), ld(p.cim), __ldg(p.logdt + d + (t128 >> 6))};
}

__device__ __forceinline__ void layer_norm16(int tid_);
__device__ __forceinline__ void kgen_powers(const ModeRaw& mr, int wg, int t128_, int row0) {
  const int t128 = opaque(t128_);
  const uint32_t scr = S_X + wg * 65536;
  const int warp = t128 >> 5, lane = t128 & 31;
  cplx cb[2], z1[2], zq[2];
  const float dt = bf_round(expf(bf2f(mr.ldt)));
  #pragma unroll
  for (int c = 0; c < 2; c++) {
    auto f = [&](uint32_t v) { return c ? bf_hi(v) : bf_lo(v); };
    const float ar = dt * f(mr.are), ai = dt * f(mr.aim);
    cb[c] = cmul({f(mr.cre), f(mr.cim)}, {dt * f(mr.bre), dt * f(mr.bim)});
    z1[c] = cexp_f(ar, ai); zq[c] = cexp_f(ar * 256.f, ai * 256.f);
  }
  uint32_t ad[8];
  #pragma unroll
  for (int i = 0; i < 8; i++) ad[i] = scr + KG_B + ((warp & 1) * 2 + (lane >> 4)) * 6144 + (warp >> 1) * 3072 + (lane & 1) * 8 + ((((lane >> 1) & 7) ^ i) << 4);
  cplx z2[2];
  {
    auto put = [&](int b, const cplx* v) { sts64(ad[b & 7] + b * 128, pack_bf16(v[0].re, -v[0].im), pack_bf16(v[1].re, -v[1].im)); };
    cplx e[2], o[2], h[2], h0[2], h4[2];
    #pragma unroll
    for (int c = 0; c < 2; c++) { z2[c] = cmul(z1[c], z1[c]); e[c] = cb[c]; o[c] = cmul(cb[c], z1[c]); }
    #pragma unroll
    for (int i = 0; i < 4; i++) {
      put(2 * i, e); put(2 * i + 1, o);
      #pragma unroll
      for (int c = 0; c < 2; c++) {
        h[c] = cmul(e[c], zq[c]);
        if (i == 0) h0[c] = h[c];
        if (i == 2) h4[c] = h[c];
        if (i < 3) { e[c] = cmul(e[c], z2[c]); o[c] = cmul(o[c], z2[c]); }
      }
      put(8 + i, h);
    }
    #pragma unroll
    for (int i = 0; i < 7; i++) {
      #pragma unroll
      for (int c = 0; c < 2; c++) { h0[c] = cmul(h0[c], zq[c]); if (i < 2) h4[c] = cmul(h4[c], zq[c]); }
      put(i < 2 ? 12 + 2 * i : 14 + i, h0);
      if (i < 2) put(13 + 2 * i, h4);
    }
  }
  if (row0 >= 0) layer_norm16(wg * 128 + t128);
  {
    #pragma unroll
    for (int i = 0; i < 8; i++) ad[i] += ((warp & 1) * 2 + (lane >> 4)) * 2048 + (warp >> 1) * 1024 - KG_B;
    cplx y[2][2], z16[2];
    #pragma unroll
    for (int c = 0; c < 2; c++) { const cplx z4 = cmul(z2[c], z2[c]); y[0][c] = {1.f, 0.f}; y[1][c] = cmul(z4, z4); z16[c] = cmul(y[1][c], y[1][c]); }
    #pragma unroll 1
    for (int jo = 0; jo < 4096; jo += 1024) {
      #pragma unroll
      for (int jj = 0; jj < 8; jj++) {
        sts64(ad[jj] + jo + jj * 128, pack_bf16(y[jj & 1][0].re, y[jj & 1][0].im), pack_bf16(y[jj & 1][1].re, y[jj & 1][1].im));
        #pragma unroll
        for (int c = 0; c < 2; c++) y[jj & 1][c] = cmul(y[jj & 1][c], z16[c]);
      }
    }
  }
  fence_async_smem();
}
__device__ __forceinline__ void kgen_finish(int wg, int t128_, bool ln) {
  const int t128 = opaque(t128_);
  const uint32_t scr = S_X + wg * 65536;
  const int warp = t128 >> 5, lane = t128 & 31;
  bar_sync(2 + wg, 128);
  float dd[24];
  {
    wg_fence();
    const uint64_t da = ((uint64_t)0x40000040u << 32) | opaque((scr >> 4) | 0x10000u), db = da + KG_B / 16;
    #pragma unroll
    for (int ks = 0; ks < 16; ks++) wgmma_ss_n48_t0(dd, da + (ks >> 2) * 512 + (ks & 3) * 2, db + (ks >> 2) * 384 + (ks & 3) * 2, ks != 0);
    wg_commit();
    wg_wait<0>();
  }
  bar_sync(2 + wg, 128);
  {
    const int g = lane >> 2, q = lane & 3, hi = warp >> 1;
    const uint32_t tb = scr + hi * KG_TAB;
    #pragma unroll
    for (int rr = 0; rr < 2; rr++) {
      const int jj = (warp & 1) * 16 + g + rr * 8;
      float v[6];
      #pragma unroll
      for (int b = 0; b < 3; b++) { v[b * 2] = hi ? dd[12 + b * 4 + rr * 2] : dd[b * 4 + rr * 2]; v[b * 2 + 1] = hi ? dd[12 + b * 4 + rr * 2 + 1] : dd[b * 4 + rr * 2 + 1]; }
      sts64(tb + (8 * jj + 2 * q) * 4, __float_as_uint(v[0]), __float_as_uint(v[1]));
      sts64(tb + (q < 2 ? 256 + 4 * jj + 2 * q : 256 + 64 * q + 2 * jj) * 4, __float_as_uint(v[2]), __float_as_uint(v[3]));
      if (q < 2) { sts32(tb + (512 + 64 * q + jj) * 4, __float_as_uint(v[4])); sts32(tb + (544 + 64 * q + jj) * 4, __float_as_uint(v[5])); }
      else if (q == 2 && jj == 0) sts32(tb + 640 * 4, __float_as_uint(v[4]));
    }
  }
  if (ln && wg == 0) mbar_wait(B_LN2, 0);
  bar_sync(2 + wg, 128);
  #pragma unroll
  for (int c = 0; c < 2; c++) {
    const uint32_t t0 = scr + c * KG_TAB, wp = s_w_of(wg * 2 + c) + 64 + t128 * 16;
    const int t = t128;
    float k0, k1, k2, k3, kp;
    if (warp < 2) {
      uint32_t a0, a1, a2, a3; lds128(t0 + 16 * t, a0, a1, a2, a3);
      k0 = __uint_as_float(a0); k1 = __uint_as_float(a1); k2 = __uint_as_float(a2); k3 = __uint_as_float(a3);
      kp = ldsf(t0 + 16 * t - (t ? 4 : 0)); if (t == 0) kp = 0.f;
    } else {
      uint32_t a0, a1; lds64(t0 + (128 + 2 * t) * 4, a0, a1);
      k0 = k1 = __uint_as_float(a0); k2 = __uint_as_float(a1); k3 = ldsf(t0 + (130 + 2 * t) * 4);
      kp = ldsf(t0 + (t == 64 ? 255 : 128 + 2 * t) * 4);
    }
    const float s0 = ldsf(t0 + (384 + t) * 4), s1 = ldsf(t0 + (385 + t) * 4);
    const int ph = t & 3, b3 = 512 + 2 * (t >> 2);
    const float a0 = ldsf(t0 + (b3 + (ph >> 1)) * 4), c0 = ldsf(t0 + (b3 + ((ph + 1) >> 1)) * 4);
    const float a1 = ldsf(t0 + (b3 + 64 + (ph >> 1)) * 4), c1 = ldsf(t0 + (b3 + 64 + ((ph + 1) >> 1)) * 4);
    sts128(wp, pack_bf16(k0, kp), pack_bf16(k1, k0), pack_bf16(k2, k1), pack_bf16(k3, k2));
    const float m = (t & 1) ? s1 : s0;
    sts128(wp + 2048, pack_bf16(s0, s0), pack_bf16(s0, s0), pack_bf16(m, s0), pack_bf16(s1, m));
    const float f0 = ph == 1 ? a0 : c0, f1 = ph == 1 ? a1 : c1;
    sts128(wp + 4096, pack_bf16(f0, a0), pack_bf16(c0, f0), pack_bf16(c0, c0), pack_bf16(c0, c0));
    sts128(wp + 6144, pack_bf16(f1, a1), pack_bf16(c1, f1), pack_bf16(c1, c1), pack_bf16(c1, c1));
    if (t < 4) sts128(wp - 64, 0, 0, 0, 0);
    if (!ln && t < 112) sts128(S_U - 3584 + c * 1792 + t * 16, 0, 0, 0, 0);
  }
}

template <int P> __device__ __forceinline__ void conv_step(float* acc, const uint32_t* fr, uint32_t db) {
  uint32_t lo; asm volatile("sub.u32 %0, %1, %2;" : "=r"(lo) : "r"(db), "n"(32 * P - 256 * 3));
  uint64_t d = ((uint64_t)0x40000040u << 32) | lo;
  #pragma unroll
  for (int sg = 3; sg >= P / 8; sg--) wgmma_rs_n32_t0(acc + 16 * sg, fr[0], fr[1], fr[2], fr[3], d - 256 * (3 - sg), P != 0);
}
template <int I, int I1> struct ConvPairs {
  static __device__ __forceinline__ void run(float* acc, const uint32_t* fr, uint32_t db) {
    conv_step<I>(acc, fr + I * 4, db); conv_step<31 - I>(acc, fr + (31 - I) * 4, db);
    ConvPairs<I + 1, I1>::run(acc, fr, db);
  }
};
template <int I1> struct ConvPairs<I1, I1> { static __device__ __forceinline__ void run(float*, const uint32_t*, uint32_t) {} };

__device__ __forceinline__ void conv_reduce(uint32_t s_r, int t128, __nv_bfloat16* yrow) {
  #pragma unroll
  for (int h = 0; h < 2; h++) {
    const int cc = t128 + h * 128;
    uint32_t v[4][4];
    #pragma unroll
    for (int b = 0; b < 4; b++) {
      lds128(s_r + b * 4096 + cc * 16, v[b][0], v[b][1], v[b][2], v[b][3]);
      if (h == 0 && b > (cc >> 1)) { v[b][0] = v[b][1] = v[b][2] = v[b][3] = 0; }
    }
    uint32_t o[4];
    #pragma unroll
    for (int e = 0; e < 4; e++) { const uint32_t p = add_bf16x2(v[0][e], v[1][e]), q = add_bf16x2(v[2][e], v[3][e]); o[e] = add_bf16x2(p, q); }
    *(uint4*)(yrow + cc * 8) = make_uint4(o[0], o[1], o[2], o[3]);
  }
}
__device__ __forceinline__ void conv_one(int wg, int c, int t128_, int uphase, __nv_bfloat16* y0) {
  const int t128 = opaque(t128_), ch = wg * 2 + c;
  const uint32_t s_w = s_w_of(ch), s_r = S_X + wg * 65536 + 49152;
  const int warp = t128 >> 5, lane = t128 & 31;
  float acc[64];
  uint32_t fr[128];
  const uint32_t wa = s_w + 64 + (warp * 16 + (lane >> 2) - 2 * (lane & 3)) * 4;
  const uint32_t zero = lds32(s_w);
  auto ld = [&](int p) { fr[p * 4] = lds32(wa + p * 256); fr[p * 4 + 1] = lds32(wa + p * 256 + 32); fr[p * 4 + 2] = lds32(wa + p * 256 - 32);
                         asm volatile("xor.b32 %0, %1, %2;" : "=r"(fr[p * 4 + 3]) : "r"(fr[p * 4]), "r"(zero)); };
  const uint32_t db = ((S_U >> 4) | 0x10000u) + ch * 2;
  #pragma unroll
  for (int p = 0; p < 32; p++) ld(p);
  if (c == 0) mbar_wait(B_U, uphase);
  mbar_wait(B_PP + 8 * wg, wg ? c ^ 1 : c);
  wg_fence();
  ConvPairs<0, 16>::run(acc, fr, db);
  wg_commit();
  if (lane == 0) mbar_arrive(B_PP + 8 - 8 * wg);
  if (c == 1) conv_reduce(s_r, t128, y0);
  wg_wait<0>();
  if (c == 1 && lane == 0) mbar_arrive(B_CDONE);
  if (c == 1) bar_sync(2 + wg, 128);
  const int col = 8 * (lane >> 4) + (lane & 7) + warp;
  const uint32_t ra = s_r + warp * 4096 + (col * 16 + ((lane >> 3) & 1) * 8) * 2;
  #pragma unroll
  for (int v = 0; v < 8; v++)
    asm volatile("stmatrix.sync.aligned.m8n8.x4.trans.shared.b16 [%0], {%1,%2,%3,%4};" :: "r"((v == 7 && col >= 16) ? S_DUMMY : ra + v * 512),
                 "r"(pack_bf16(acc[v * 8], acc[v * 8 + 1])), "r"(pack_bf16(acc[v * 8 + 2], acc[v * 8 + 3])), "r"(pack_bf16(acc[v * 8 + 4], acc[v * 8 + 5])), "r"(pack_bf16(acc[v * 8 + 6], acc[v * 8 + 7])) : "memory");
  bar_sync(2 + wg, 128);
}

__device__ __forceinline__ void layer_norm16(int tid_) {
  const int tid = opaque(tid_), row = tid >> 4, l16 = tid & 15;
  const uint32_t ra = S_LN + (l16 >> 3) * 2048 + row * 128 + (((l16 & 7) ^ (row & 7)) << 4);
  uint32_t v[20];
  mbar_wait(B_RAW, 0);
  #pragma unroll
  for (int i = 0; i < 4; i++) lds128(ra + i * 4096, v[i * 4], v[i * 4 + 1], v[i * 4 + 2], v[i * 4 + 3]);
  v[16] = v[17] = v[18] = v[19] = 0;
  if (l16 < 8) lds128(ra + 16384, v[16], v[17], v[18], v[19]);
  float s0 = 0.f, s1 = 0.f, q0 = 0.f, q1 = 0.f;
  #pragma unroll
  for (int e = 0; e < 20; e++) { const float lo = bf_lo(v[e]), hi = bf_hi(v[e]); s0 += lo; s1 += hi; q0 = fmaf(lo, lo, q0); q1 = fmaf(hi, hi, q1); }
  float s = s0 + s1, ss = q0 + q1;
  #pragma unroll
  for (int o = 8; o; o >>= 1) { s += __shfl_xor_sync(0xffffffffu, s, o); ss += __shfl_xor_sync(0xffffffffu, ss, o); }
  const float mean = s * (1.f / D_), var = fmaxf(fmaf(-mean, mean, ss * (1.f / D_)), 0.f);
  const uint32_t mb = pack_bf16(mean, mean);
  const float rs = 1.0f / bf_round(sqrtf(bf_round(bf_round(var) + 1e-5f)));
  const uint32_t rh = pack_bf16(rs, rs), rl = pack_bf16(rs - bf_lo(rh), rs - bf_lo(rh));
  #pragma unroll
  for (int e = 0; e < 20; e++) { const uint32_t dd = sub_bf16x2(v[e], mb); asm("fma.rn.bf16x2 %0, %1, %2, %3;" : "=r"(v[e]) : "r"(dd), "r"(rh), "r"(mul_bf16x2(dd, rl))); }
  #pragma unroll
  for (int i = 0; i < 5; i++) if (i < 4 || l16 < 8) sts128(ra + i * 4096, v[i * 4], v[i * 4 + 1], v[i * 4 + 2], v[i * 4 + 3]);
  bar_sync(4, 256);
  {
    const int warp = tid >> 5, lane = tid & 31, r = lane & 7, e = lane >> 3, tok = (r >> 1) * 4 + (r & 1) + (e & 1) * 2;
    const uint32_t la = S_LN + (warp >> 2) * 2048 + tok * 128 + ((((warp & 3) * 2 + (e >> 1)) ^ (tok & 7)) << 4), ta = S_LN + 18432 + warp * 512 + lane * 8;
    #pragma unroll
    for (int i = 0; i < 5; i++) if (i < 4 || warp < 4) ldsm_x4t(la + i * 4096, v[i * 4], v[i * 4 + 1], v[i * 4 + 2], v[i * 4 + 3]);
    #pragma unroll
    for (int i = 0; i < 5; i++) if (i < 4 || warp < 4) { sts64(ta + i * 4096, v[i * 4], v[i * 4 + 1]); sts64(ta + i * 4096 + 256, v[i * 4 + 2], v[i * 4 + 3]); }
  }
  fence_async_smem();
  __syncwarp();
  if ((tid & 31) == 0) mbar_arrive(B_LN);
}

__device__ __forceinline__ void ssm_phase(const SsmParams& p, ModeRaw mr, int wg, int d0, int npair, int row0, int t128) {
  int d = d0 + wg * 2;
  #pragma unroll 1
  for (int it = 0; it < npair; it++, d += 4) {
    kgen_powers(mr, wg, t128, row0);
    kgen_finish(wg, t128, row0 >= 0);
    fence_async_smem();
    __syncwarp();
    if ((t128 & 31) == 0) mbar_arrive(B_KDONE + 8 * wg);
    bar_sync(2 + wg, 128);
    #pragma unroll 1
    for (int c = 0; c < 2; c++) conv_one(wg, c, t128, it & 1, g_yt + d * L_);
    conv_reduce(S_X + wg * 65536 + 49152, opaque(t128), g_yt + (d + 1) * L_);
    fence_async_smem();
    __syncwarp();
    if ((t128 & 31) == 0) mbar_arrive(B_RDONE + 8 * wg);
    if (it + 1 < npair) { mr = load_mode(p, d + 4, t128); bar_sync(4, 256); }
  }
  if ((t128 & 31) == 0) mbar_arrive(B_YDONE);
}

struct Ring { bool ready; };
__device__ __forceinline__ void arrive_one(uint32_t bar) {
  asm volatile("{\n.reg .pred p;\nelect.sync _|p, 0xffffffff;\n@p mbarrier.arrive.shared::cta.b64 _, [%0];\n}\n" :: "r"(bar) : "memory");
}

template <int PH, int KB0 = 0, int KB1 = 6, bool FIRST = false, bool LAST = false, class Pre, class Slice>
__device__ __forceinline__ void run_pass(float* acc, uint32_t* a, Ring& r, Pre pre, Slice slice) {
  #pragma unroll
  for (int kb = KB0; kb < KB1; kb++) {
    pre(kb);
    if (!r.ready) mbar_wait(B_FULL + 8 * kb, PH);
    wg_fence();
    const uint64_t d0 = ((uint64_t)0x40000040u << 32) | ((S_RING + kb * STG_BYTES) >> 4) | (512u << 16);
    #pragma unroll
    for (int kk = 0; kk < 6; kk++) {
      wgmma_rs_n64_t1(acc, a[(kb * 6 + kk) * 4 + 0], a[(kb * 6 + kk) * 4 + 1], a[(kb * 6 + kk) * 4 + 2], a[(kb * 6 + kk) * 4 + 3], d0 + kk * 128, (kb | kk) != 0);
      if (kk == SLPOS) slice(kb);
    }
    wg_commit();
    if (!LAST) r.ready = mbar_try_wait(B_FULL + 8 * ((kb + 1) % 6), kb == 5 ? PH ^ 1 : PH);
    if (kb > 0 || !FIRST) {
      wg_wait<1>();
      arrive_one(B_EMPTY + 8 * ((kb + 5) % 6));
    }
  }
}

struct CtaId { int m, j; };
__device__ __forceinline__ CtaId map_cta(int bx) { return {bx & 15, bx >> 4}; }
__device__ __forceinline__ CtaId cta_id() {
  int bx; asm volatile("mov.u32 %0, %%ctaid.x;" : "=r"(bx));
  bx = __shfl_sync(0xffffffffu, bx, 0);
  return map_cta(bx);
}
__device__ __forceinline__ CtaId cta_id_lane() {
  int bx; asm volatile("mov.u32 %0, %%ctaid.x;" : "=r"(bx));
  return map_cta(bx);
}
struct Maps { CUtensorMap xraw3, x2, xt, xt64, xt8, yt, w1, w3, w2, x8, yt8; };

__global__ void __launch_bounds__(NTHR, 1) k_main(const __grid_constant__ Maps tm, const SsmParams sp, const __nv_bfloat16* __restrict__ dskip,
                                                   __nv_bfloat16* __restrict__ out) {
  extern __shared__ unsigned char smem_raw[];
  const int tid = threadIdx.x, wg = __shfl_sync(0xffffffffu, tid >> 7, 0);
  const int bx = blockIdx.x;
  const bool ffn = bx < NFFN;
  const int m = map_cta(bx).m, j = map_cta(bx).j;
  const int d0 = ffn ? bx * 4 : 512 + (bx - NFFN) * 16, npair = ffn ? 1 : 4;
  if (smem_u32(smem_raw) != S_X) return;
  if (wg == 2) {
    asm volatile("setmaxnreg.dec.sync.aligned.u32 24;");
    if (tid == 256) {
      mbar_init(B_RAW, 1);
      asm volatile("fence.mbarrier_init.release.cluster;" ::: "memory");
      if (ffn) { mbar_expect_tx(B_RAW, 18432); tma3d(S_LN, &tm.xraw3, 0, m * 128 + j * 16, 0, B_RAW); }
    } else if (tid >= 288 && tid < 336) {
      const int bi = tid - 288;
      const uint64_t tab = bi < 16 ? 0x88888800111111ull : (bi < 32 ? 0x8440180028011111ull : 0x111188814481440ull);
      const uint32_t c = (uint32_t)(tab >> (4 * (bi & 15))) & 15u;
      if (c) mbar_init(S_BAR + 8 * bi, (bi == 27 && ffn) ? 2 : c);
      asm volatile("fence.mbarrier_init.release.cluster;" ::: "memory");
    }
    bar_sync(0, NTHR);
    const int pw = (tid >> 5) & 3, lane = tid & 31;
    if (pw == 0) {
      if (lane == 0) {
        auto wload0 = [&](int kb0) {
          #pragma unroll 1
          for (int kb = kb0; kb < kb0 + 3; kb++) { mbar_expect_tx(B_FULL + 8 * kb, STG_BYTES); tma2d(S_RING + kb * STG_BYTES, &tm.w1, j * 576, kb * 96, B_FULL + 8 * kb); }
        };
        const unsigned int epoch = cur_epoch();
        if (ffn) {
          mbar_wait_long(B_RAW, 0);
          wload0(0);
        }
        if (ffn) mbar_wait_long(B_LN2, 0); else __nanosleep(2500);
        #pragma unroll 1
        for (int it = 0; it < 8192; it++) { unsigned int v; asm volatile("ld.acquire.gpu.global.u32 %0, [%1];" : "=r"(v) : "l"(&g_cnt_all) : "memory"); if (v == epoch * NFFN) break; }
        fence_async();
        #pragma unroll 1
        for (int it = 0; it < npair; it++) {
          if (it > 0) mbar_wait_long(B_CDONE, (it - 1) & 1);
          mbar_expect_tx(B_U, 16384);
          tma2d(S_U, &tm.xt, (d0 + it * 4) * 16, 0, B_U);
        }
        if (ffn) {
          #pragma unroll 1
          for (int w = 0; w < 2; w++) {
            mbar_wait_long(B_KDONE + 8 * w, 0);
            mbar_expect_tx(B_X + 8 * w, 3 * 16384);
            #pragma unroll 1
            for (int q = 0; q < 3; q++) tma3d(S_X + w * 65536 + q * 16384, &tm.xt64, 0, (w * 3 + q) * 16, m * 8, B_X + 8 * w);
          }
          mbar_wait_long(B_CDONE, 0);
          wload0(3);
          #pragma unroll 1
          for (int w = 0; w < 3; w++) {
            if (w > 0) mbar_wait_long(B_RDONE - 8 + 8 * w, 0);
            const uint32_t bar = B_X + (w ? 8 + 8 * w : 32);
            mbar_expect_tx(bar, 16384); tma3d(S_X + (w ? 4 * w - 1 : 8) * 16384, &tm.xt64, 0, w ? 80 + 16 * w : 128, m * 8, bar);
          }
          auto wpass = [&](const CUtensorMap* t, int c0, int c1, uint32_t par) {
            #pragma unroll
            for (int kb = 0; kb < 6; kb++) {
              mbar_spin(B_EMPTY + 8 * kb, par);
              mbar_expect_tx(B_FULL + 8 * kb, STG_BYTES);
              tma2d(S_RING + kb * STG_BYTES, t, c0, c1 + kb * 96, B_FULL + 8 * kb);
            }
          };
          const CUtensorMap* t = &tm.w3; int c0 = j * 576, c1 = 0;
          #pragma unroll 1
          for (int p = 1; p < 27; p++) {
            wpass(t, c0, c1, (p - 1) & 1);
            if (p < 17) { t = (p & 1) ? &tm.w1 : &tm.w3; c0 += (p & 1) * 64; }
            else { t = &tm.w2; c1 = j * 576; c0 = p == 17 ? 512 : ((j + p - 17) & 7) * 64; }
          }
        }
      }
      __syncwarp();
    } else {
      const int hw = pw - 1;
      if (tid == 352) { sts32(S_DSK + 196, atomicAdd(&g_ticket, 1) / NCTA + 1); mbar_arrive(B_EP); }
      if (tid == 320) { prefetch_tmap(&tm.xt); prefetch_tmap(&tm.w1); prefetch_tmap(&tm.xt64); prefetch_tmap(&tm.w3); }
      __syncwarp();
      if (hw == 0) {
        const unsigned int epoch = cur_epoch();
        if (ffn) { const uint32_t* dp = (const uint32_t*)dskip; sts32(S_DSK + lane * 4, __ldg(dp + j * 32 + (lane & 24) + ((lane >> 1) & 3) + (lane & 1) * 4)); if (lane < 4) sts32(S_DSK + 128 + lane * 4, __ldg(dp + 256 + j * 4 + lane)); }
        if (ffn && lane == 0) {
          mbar_wait_long(B_LN, 0);
          asm volatile("cp.async.bulk.global.shared::cta.bulk_group [%0], [%1], %2;" :: "l"(g_xt + (m * 128 + j * 16) * D_), "r"(S_LN + 18432), "r"(18432) : "memory");
          asm volatile("cp.async.bulk.commit_group;" ::: "memory");
          asm volatile("cp.async.bulk.wait_group 0;" ::: "memory");
          fence_async();
          red_add(&g_cnt_all);
          mbar_arrive(B_LN2);
        }
        __syncwarp();
        if (ffn) {
          #pragma unroll
          for (int i = 0; i < 7; i++) sts128(S_U - 3584 + i * 512 + lane * 16, 0, 0, 0, 0);
          fence_async_smem();
          __syncwarp();
          if (lane == 0) mbar_arrive(B_U);
        }
        mbar_wait_long(B_CDONE, 0);
        if (ffn) {
          uint4* za = g_acc + (m * 9 + j) * 1024 + lane;
          #pragma unroll 1
          for (int i = 0; i < 32; i++) za[i * 32] = make_uint4(0, 0, 0, 0);
          za = g_acc + (m * 9 + 8) * 1024 + j * 128 + lane;
          #pragma unroll 1
          for (int i = 0; i < 4; i++) za[i * 32] = make_uint4(0, 0, 0, 0);
        }
        __syncwarp();
        if (lane == 0) {
          mbar_wait_long(B_YDONE, 0);
          fence_gpu(); red_add(ffn ? &g_cnt_y : &g_cnt_ys);
          if (ffn) {
            prefetch_tmap(&tm.x2); prefetch_tmap(&tm.yt); prefetch_tmap(&tm.x8); prefetch_tmap(&tm.xt8); prefetch_tmap(&tm.yt8); prefetch_tmap(&tm.w2);
            flag_wait(&g_cnt_y, epoch * NFFN, 500); fence_async();
            mbar_arrive(B_GO);
            mbar_wait_long(B_PFREE, 0);
            mbar_expect_tx(B_H, 49152);
            __nanosleep(PACE); tma2d(S_X + 2 * 16384, &tm.x2, j * 64, m * 128, B_H); __nanosleep(PACE); tma3d(S_X + 3 * 16384, &tm.xt64, 0, j * 16, m * 8, B_H); __nanosleep(PACE);
            tma2d(S_X + 4 * 16384, &tm.yt, m * 128, j * 64, B_H); tma2d(S_X + 4 * 16384 + 8192, &tm.yt, m * 128 + 64, j * 64, B_H);
            #pragma unroll 1
            for (int k = 0; k < 3; k++) {
              mbar_wait_long(B_PUB + 8 * k, 0);
              fence_gpu();
              red_add(&g_cnt_acc[(m * 9 + (k ? (j + 2 * k) & 7 : 8)) * 8]);
              if (k < 2) red_add(&g_cnt_acc[(m * 9 + ((j + 2 * k + 1) & 7)) * 8]);
            }
            flag_wait(&g_cnt_acc[(m * 9 + j) * 8], epoch * 4, 50); fence_async();
            mbar_expect_tx(B_R, 16384); bulk_g2s(S_X + 6 * 16384, g_acc + (m * 9 + j) * 1024, 16384, B_R);
          }
        }
        __syncwarp();
      }
      if (ffn) {
        if (hw == 1 && lane == 0) {
          const CtaId id = cta_id_lane();
          mbar_wait_long(B_RAW, 0);
          #pragma unroll 1
          for (int p = 0; p < 27; p++) {
            if (p > PFLA) mbar_wait_long(B_FULL, (p - PFLA - 1) & 1);
            const int kb = (id.m - p * 6) & 15;
            if (kb < 6) {
              const CUtensorMap* t = p < 18 ? ((p & 1) ? &tm.w3 : &tm.w1) : &tm.w2;
              const int c0 = p < 18 ? id.j * 576 + (p >> 1) * 64 : (p == 18 ? 8 : ((id.j + p - 18) & 7)) * 64, c1 = (p < 18 ? 0 : id.j * 576) + kb * 96;
              asm volatile("cp.async.bulk.prefetch.tensor.2d.L2.global [%0, {%1, %2}];" :: "l"(t), "r"(c0), "r"(c1) : "memory");
            }
          }
        }
        __syncwarp();
        if (hw > 0) {
          mbar_wait_long(B_H, 0);
          {
            const uint32_t r7 = lane & 7, dq = (lane >> 4) * 2 + (r7 >> 2);
            const uint32_t na = S_X + 3 * 16384 + dq * 128 + ((((lane & 3) * 2 + ((lane >> 3) & 1)) ^ dq) << 4);
            const uint32_t ya = S_X + 4 * 16384 + ((lane >> 4) * 8 + r7) * 128 + ((((lane >> 3) & 1) ^ r7) << 4);
            const uint32_t xa = S_X + 2 * 16384 + (lane & 15) * 128 + (((lane >> 4) ^ r7) << 4);
            #pragma unroll 1
            for (int k = __shfl_sync(0xffffffffu, hw == 1 ? 0 : BSPLIT, 0), k1_ = __shfl_sync(0xffffffffu, hw == 1 ? BSPLIT : 32, 0); k < k1_; k++) {
              const uint32_t hf = (k >> 4) * 8192, i = (k >> 2) & 3, wp = k & 3;
              uint32_t x[4], n[4], y[4], k0, k1;
              ldsm_x4t((na ^ ((i & 1) * 64)) + hf + wp * 2048 + i * 512, n[0], n[1], n[2], n[3]);
              ldsm_x4t((ya ^ (wp * 32)) + hf + i * 2048, y[0], y[1], y[2], y[3]);
              ldsm_x4((xa ^ (i * 32)) + hf + wp * 2048, x[0], x[1], x[2], x[3]);
              lds64(S_DSK + i * 32 + (lane & 3) * 8, k0, k1);
              sts128(S_X + 7 * 16384 + k * 512 + lane * 16, add_bf16x2(x[0], add_bf16x2(y[0], mul_bf16x2(n[0], k0))), add_bf16x2(x[1], add_bf16x2(y[1], mul_bf16x2(n[1], k0))),
                     add_bf16x2(x[2], add_bf16x2(y[2], mul_bf16x2(n[2], k1))), add_bf16x2(x[3], add_bf16x2(y[3], mul_bf16x2(n[3], k1))));
            }
          }
          __syncwarp();
          if (lane == 0) {
            mbar_arrive(B_BASE);
            const CtaId id = cta_id_lane();
            const unsigned int epoch = cur_epoch();
            if (hw == 2) {
              flag_wait(&g_cnt_ys, epoch * (NCTA - NFFN), 300);
              flag_wait(&g_cnt_acc[(id.m * 9 + 8) * 8], epoch * 8, 300); fence_async();
              mbar_expect_tx(B_H8, 8192);
              tma2d(S_X + 8 * 16384, &tm.x8, 512 + id.j * 8, id.m * 128, B_H8); tma3d(S_X + 8 * 16384 + 2048, &tm.xt8, 0, 128 + id.j * 2, id.m * 8, B_H8);
              tma2d(S_X + 8 * 16384 + 4096, &tm.yt8, id.m * 128, 512 + id.j * 8, B_H8); tma2d(S_X + 8 * 16384 + 5120, &tm.yt8, id.m * 128 + 64, 512 + id.j * 8, B_H8);
              bulk_g2s(S_X + 8 * 16384 + 6144, g_acc + (id.m * 9 + 8) * 1024 + id.j * 128, 2048, B_H8);
            }
          }
          __syncwarp();
          if (hw == 2) {
            mbar_wait_long(B_H8, 0);
            const CtaId id = cta_id();
            const uint32_t h2 = (lane >> 2) & 1, hb = (lane >> 3) & 1;
            const uint32_t ta = (lane & 16) ? S_X + 8 * 16384 + 4096 + (lane & 7) * 128 + ((hb ^ (lane & 7)) << 4) : S_X + 8 * 16384 + 2048 + h2 * 128 + ((((lane & 3) * 2 + hb) ^ h2) << 4);
            const uint32_t k0 = lds32(S_DSK + 128 + (lane & 3) * 4);
            __nv_bfloat16* op = out + (id.m * 128 * D_ + 512 + id.j * 8) + (lane >> 2) * D_ + (lane & 3) * 2;
            #pragma unroll 1
            for (int k = 0; k < 8; k++, op += 16 * D_) {
              uint32_t x0, x1, n0, n1, y0, y1, v0, v1;
              asm volatile("ldmatrix.sync.aligned.m8n8.x2.shared.b16 {%0,%1}, [%2];" : "=r"(x0), "=r"(x1) : "r"(S_X + 8 * 16384 + k * 256 + (lane & 15) * 16) : "memory");
              ldsm_x4t((ta ^ ((k & 3) * 32)) + ((lane & 16) ? (k >> 2) * 1024 : k * 256), n0, n1, y0, y1);
              lds64(S_X + 8 * 16384 + 6144 + k * 256 + lane * 8, v0, v1);
              *(uint32_t*)op = add_bf16x2(add_bf16x2(x0, add_bf16x2(y0, mul_bf16x2(n0, k0))), v0);
              *(uint32_t*)(op + 8 * D_) = add_bf16x2(add_bf16x2(x1, add_bf16x2(y1, mul_bf16x2(n1, k0))), v1);
            }
          }
        }
      }
    }
  } else {
    asm volatile("setmaxnreg.inc.sync.aligned.u32 240;");
    const ModeRaw mr0 = load_mode(sp, d0 + wg * 2, tid & 127);
    bar_sync(0, NTHR);
    const int t128 = tid & 127, warp = t128 >> 5, lane = tid & 31;
    ssm_phase(sp, mr0, wg, d0, npair, ffn ? m * 128 + j * 16 : -1, t128);
    if (ffn) {
    uint32_t a[144];
    float accG[32], accU[32];
    Ring r{false};
    const uint32_t park = S_X + wg * 8192 + t128 * 16;
    auto nop = [](int) {};
    auto silu_slice = [&](int kb, int t) {
      if (kb >= 1 && kb <= 4) {
        const int i0 = (kb - 1) * 8;
        sts128(park + t * 16384 + (kb - 1) * 2048, pack_bf16(silu_f(accG[i0]), silu_f(accG[i0 + 1])), pack_bf16(silu_f(accG[i0 + 2]), silu_f(accG[i0 + 3])),
               pack_bf16(accG[i0 + 4], accG[i0 + 5]), pack_bf16(accG[i0 + 6], accG[i0 + 7]));
      }
    };
    auto mul_unit = [&](int i, int t, uint32_t& h0, uint32_t& h1, uint32_t& h2, uint32_t& h3) {
      uint32_t s0, s1, g2, g3; const int i0 = i * 8;
      lds128(park + t * 16384 + i * 2048, s0, s1, g2, g3);
      h0 = mul_bf16x2(s0, pack_bf16(accU[i0], accU[i0 + 1])); h1 = mul_bf16x2(s1, pack_bf16(accU[i0 + 2], accU[i0 + 3]));
      h2 = mul_bf16x2(pack_bf16(silu_f(bf_lo(g2)), silu_f(bf_hi(g2))), pack_bf16(accU[i0 + 4], accU[i0 + 5]));
      h3 = mul_bf16x2(pack_bf16(silu_f(bf_lo(g3)), silu_f(bf_hi(g3))), pack_bf16(accU[i0 + 6], accU[i0 + 7]));
    };
    {
      const uint32_t xrow = (lane >> 4) * 2 + ((lane >> 2) & 1);
      const uint32_t rbase = S_X + wg * 8192 + warp * 2048 + xrow * 128 + ((((lane & 3) * 2 + ((lane >> 3) & 1)) ^ xrow) << 4);
      auto ldx = [&](int kb) {
          if (kb == 0) mbar_wait(B_X, 0);
          if (kb == 2) mbar_wait(B_X + 8, 0);
          if (kb == 4) { mbar_wait(B_X + 16, 0); mbar_wait(B_X + 24, 0); }
          if (kb == 5) mbar_wait(B_X + 32, 0);
          #pragma unroll
          for (int kk = 0; kk < 6; kk++) {
            const int ks = kb * 6 + kk;
            ldsm_x4t((rbase ^ ((ks & 1) * 64)) + xslot(ks >> 2) * 16384 + (ks & 3) * 512, a[ks * 4 + 0], a[ks * 4 + 1], a[ks * 4 + 2], a[ks * 4 + 3]);
          }
        };
      run_pass<0, 0, 5, true>(accG, a, r, ldx, nop);
      ldx(5);
    }
    bar_sync(2 + wg, 128);
    auto reload = [&](int grp, int on) {
      #pragma unroll
      for (int i = 0; i < 6; i++) {
        const int q = grp * 6 + i;
        if (q < 32) asm volatile("{\n.reg .pred p;\nsetp.ne.b32 p, %5, 0;\n@p ld.shared.v4.b32 {%0,%1,%2,%3}, [%4];\n}\n"
                                 : "+r"(a[q * 4]), "+r"(a[q * 4 + 1]), "+r"(a[q * 4 + 2]), "+r"(a[q * 4 + 3]) : "r"(park + (q >> 2) * 16384 + (q & 3) * 2048), "r"(on) : "memory");
      }
    };
    #pragma unroll 1
    for (int t = 0; t < 9; t++) {
      run_pass<0, 5, 6>(accG, a, r, nop, nop);
      run_pass<1>(accU, a, r, nop, [&](int kb) { silu_slice(kb, t); if (kb >= 2) reload(kb - 2, t == 8); });
      run_pass<0, 0, 5>(accG, a, r, nop, [&](int kb) {
        if (kb <= 1) reload(4 + kb, t == 8);
        if (kb >= 1) {
          uint32_t h0, h1, h2, h3; mul_unit(kb - 1, t, h0, h1, h2, h3);
          sts128(park + t * 16384 + (kb - 1) * 2048, h0, h1, h2, h3);
          asm volatile("{\n.reg .pred p;\nsetp.ne.b32 p, %8, 0;\n@p mov.b32 %0, %4;\n@p mov.b32 %1, %5;\n@p mov.b32 %2, %6;\n@p mov.b32 %3, %7;\n}\n"
                       : "+r"(a[124 + kb * 4]), "+r"(a[125 + kb * 4]), "+r"(a[126 + kb * 4]), "+r"(a[127 + kb * 4]) : "r"(h0), "r"(h1), "r"(h2), "r"(h3), "r"((int)(t == 8)));
        } });
    }
    fence_async_smem(); __syncwarp(); arrive_one(B_PFREE);
    const uint32_t tag = opaque(cur_epoch() & 1);
    const CtaId id2 = cta_id(); const int m = id2.m, j = id2.j;
    const uint32_t pk = park - S_X;
    auto store_vec = [&](const float* acc, int t, int i, bool may0) {
      uint32_t w0 = pack_bf16(acc[i * 8], acc[i * 8 + 1]), w1 = pack_bf16(acc[i * 8 + 2], acc[i * 8 + 3]), w2 = pack_bf16(acc[i * 8 + 4], acc[i * 8 + 5]), w3 = pack_bf16(acc[i * 8 + 6], acc[i * 8 + 7]);
      if (may0 && __builtin_expect(t == 0, 0)) {
        if (i == 0) mbar_wait(B_GO, 0);
        const uint32_t pq = opaque(pk);
        char* dst = (char*)g_acc + (size_t)(m * 9 + 8) * 16384 + i * 4096 + (((pq >> 1) & 1023) | ((pq >> 3) & 1024));
        asm volatile("red.relaxed.gpu.global.add.noftz.v2.bf16x2 [%0], {%1,%2};" :: "l"(dst), "r"(w0), "r"(w1) : "memory");
        asm volatile("red.relaxed.gpu.global.add.noftz.v2.bf16x2 [%0], {%1,%2};" :: "l"(dst + 2048), "r"(w2), "r"(w3) : "memory");
      } else {
        const int blk = (j + t) & 7;
        const char* base = t >= 5 ? (const char*)g_part + (size_t)((m * 8 + blk) * 3 + t - 5) * 16384 : (const char*)g_acc + (size_t)(m * 9 + blk) * 16384;
        asm volatile("{\n.reg .pred p;\n.reg .b32 a, b, c, d;\nsetp.ge.s32 p, %6, 5;\n"
                     "lop3.b32 a, %1, -2, %5, 0xEA;\nlop3.b32 b, %2, -2, %5, 0xEA;\nlop3.b32 c, %3, -2, %5, 0xEA;\nlop3.b32 d, %4, -2, %5, 0xEA;\n"
                     "@p st.relaxed.gpu.global.v4.b32 [%0], {a,b,c,d};\n@!p red.relaxed.gpu.global.add.noftz.v4.bf16x2 [%0], {%1,%2,%3,%4};\n}\n"
                     :: "l"(base + i * 2048 + pk), "r"(w0), "r"(w1), "r"(w2), "r"(w3), "r"(tag), "r"(t) : "memory");
        if (i == 3) { __syncwarp(); asm volatile("{\n.reg .pred p, q;\nelect.sync _|p, 0xffffffff;\nsetp.ne.and.b32 q, %1, 0, p;\n@q mbarrier.arrive.shared::cta.b64 _, [%0];\n}\n" :: "r"(B_PUB + 8 * (t >> 1)), "r"((int)(t < 5 && t != 2)) : "memory"); }
      }
    };
    auto own_part = [&](int s) { return (const char*)g_part + (size_t)((m * 8 + j) * 3 + s - 5) * 16384 + pk; };
    auto fetch = [&](int s) {
      const char* src = own_part(s);
      #pragma unroll
      for (int i = 0; i < 4; i++) cp_async16(park + (s == 7 ? 5 : (s & 1)) * 16384 + i * 2048, src + i * 2048);
      cp_commit();
    };
    uint32_t missing = 0;
    auto final_vec = [&](int i) {
      uint32_t v[4], f[4], b[4];
      lds128(park + 16384 + i * 2048, v[0], v[1], v[2], v[3]);
      lds128(park + 6 * 16384 + i * 2048, f[0], f[1], f[2], f[3]); lds128(park + 7 * 16384 + i * 2048, b[0], b[1], b[2], b[3]);
      if (tag_bad(v[0], v[1], v[2], v[3], tag)) missing |= 1u << i;
      else sts128(park + 6 * 16384 + i * 2048, add_bf16x2(f[0], v[0]), add_bf16x2(f[1], v[1]), add_bf16x2(f[2], v[2]), add_bf16x2(f[3], v[3]));
      #pragma unroll
      for (int e = 0; e < 4; e++) { accU[i * 8 + 2 * e] = bf_lo(b[e]); accU[i * 8 + 2 * e + 1] = bf_hi(b[e]); }
    };
    #pragma unroll 1
    for (int u = 1; u < 7; u += 2) {
      run_pass<0, 5, 6>(accG, a, r, nop, nop);
      run_pass<1>(accU, a, r, nop, [&](int kb) { if (kb >= 1 && kb <= 4) store_vec(accG, u - 1, kb - 1, true); });
      run_pass<0, 0, 5>(accG, a, r, nop, [&](int kb) { if (kb >= 1) store_vec(accU, u, kb - 1, false); });
    }
    run_pass<0, 5, 6>(accG, a, r, nop, nop);
    run_pass<1>(accU, a, r, nop, [&](int kb) { if (kb >= 1 && kb <= 4) store_vec(accG, 6, kb - 1, false); if (kb == 5) fetch(5); });
    run_pass<0, 0, 5>(accG, a, r, nop, [&](int kb) {
      if (kb == 0) { wg_wait<0>(); store_vec(accU, 7, 0, false); store_vec(accU, 7, 1, false); }
      if (kb == 1) { store_vec(accU, 7, 2, false); store_vec(accU, 7, 3, false); fetch(6); }
      if (kb == 2) { mbar_wait(B_BASE, 0); mbar_wait(B_R, 0); cp_wait<1>(); }
      if (kb >= 2) final_vec(kb - 2);
      if (kb == 4) fetch(7); });
    {
      run_pass<0, 5, 6, false, true>(accG, a, r, nop, [&](int) { final_vec(3); });
      cp_wait<0>();
      #pragma unroll
      for (int i = 0; i < 4; i++) {
        uint32_t v[4], w[4], f[4]; lds128(park + i * 2048, w[0], w[1], w[2], w[3]); lds128(park + 5 * 16384 + i * 2048, v[0], v[1], v[2], v[3]); lds128(park + 6 * 16384 + i * 2048, f[0], f[1], f[2], f[3]);
        if (tag_bad(w[0], w[1], w[2], w[3], tag)) { missing |= 16u << i; w[0] = w[1] = w[2] = w[3] = 0; }
        if (tag_bad(v[0], v[1], v[2], v[3], tag)) { missing |= 256u << i; v[0] = v[1] = v[2] = v[3] = 0; }
        add_vec(accU + i * 8, add_bf16x2(f[0], add_bf16x2(v[0], w[0])), add_bf16x2(f[1], add_bf16x2(v[1], w[1])), add_bf16x2(f[2], add_bf16x2(v[2], w[2])), add_bf16x2(f[3], add_bf16x2(v[3], w[3])));
      }
      #pragma unroll 1
      for (int it = 0; missing && it < 4096; it++) {
        const int s = (__ffs(missing) - 1) >> 2;
        const uint4* src = (const uint4*)own_part(5 + s);
        uint32_t v[16];
        #pragma unroll
        for (int i = 0; i < 4; i++) ld_relaxed_v4(src + i * 128, v[i * 4], v[i * 4 + 1], v[i * 4 + 2], v[i * 4 + 3]);
        #pragma unroll
        for (int i = 0; i < 4; i++)
          if ((missing >> (4 * s + i) & 1) && !tag_bad(v[i * 4], v[i * 4 + 1], v[i * 4 + 2], v[i * 4 + 3], tag)) { add_vec(accU + i * 8, v[i * 4], v[i * 4 + 1], v[i * 4 + 2], v[i * 4 + 3]); missing &= ~(1u << (4 * s + i)); }
      }
      __syncwarp();
      wg_wait<0>();
      #pragma unroll
      for (int i = 0; i < 32; i++) accU[i] += accG[i];
      const uint32_t pq = opaque(pk); const int lane = (pq >> 4) & 31, warp = (pq >> 9) & 3, wg = pq >> 13;
      const uint32_t stg = S_X + 4 * 16384 + wg * 8192 + warp * 2048;
      #pragma unroll
      for (int i = 0; i < 4; i++) {
        const int row = (lane & 7) + ((lane >> 3) & 1) * 8, chunk = 2 * i + (lane >> 4);
        asm volatile("stmatrix.sync.aligned.m8n8.x4.shared.b16 [%0], {%1,%2,%3,%4};" :: "r"(stg + row * 128 + ((chunk ^ (row & 7)) << 4)),
                     "r"(pack_bf16(accU[i * 8], accU[i * 8 + 1])), "r"(pack_bf16(accU[i * 8 + 2], accU[i * 8 + 3])), "r"(pack_bf16(accU[i * 8 + 4], accU[i * 8 + 5])), "r"(pack_bf16(accU[i * 8 + 6], accU[i * 8 + 7])) : "memory");
      }
      __syncwarp();
      #pragma unroll
      for (int i = 0; i < 4; i++) {
        const int row = i * 4 + (lane >> 3), chunk = lane & 7;
        uint32_t o0, o1, o2, o3; lds128(stg + row * 128 + ((chunk ^ (row & 7)) << 4), o0, o1, o2, o3);
        *(uint4*)(out + (m * 128 + wg * 64 + warp * 16 + row) * D_ + j * 64 + chunk * 8) = make_uint4(o0, o1, o2, o3);
      }
    }
    }
  }
}

typedef CUresult (*EncFn)(CUtensorMap*, CUtensorMapDataType, cuuint32_t, void*, const cuuint64_t*, const cuuint64_t*, const cuuint32_t*, const cuuint32_t*, CUtensorMapInterleave, CUtensorMapSwizzle, CUtensorMapL2promotion, CUtensorMapFloatOOBfill);
static void enc(EncFn f, CUtensorMap* tm, const void* base, int rank, uint64_t d0, uint64_t d1, uint64_t d2, uint64_t s1, uint64_t s2, uint32_t b0, uint32_t b1, uint32_t b2, CUtensorMapSwizzle sw) {
  cuuint64_t dims[3] = {d0, d1, d2}; cuuint64_t strides[2] = {s1, s2}; cuuint32_t box[3] = {b0, b1, b2}; cuuint32_t es[3] = {1, 1, 1};
  CUresult r = f(tm, CU_TENSOR_MAP_DATA_TYPE_BFLOAT16, rank, (void*)base, dims, strides, box, es, CU_TENSOR_MAP_INTERLEAVE_NONE, sw, CU_TENSOR_MAP_L2_PROMOTION_L2_128B, CU_TENSOR_MAP_FLOAT_OOB_FILL_NONE);
  if (r != CUDA_SUCCESS) fprintf(stderr, "tensor map encode failed %d\n", (int)r);
}

extern "C" void kernel_launch(void* const* d_in, const int* in_sizes, int n_in, void* d_out, int out_size) {
  static const void* key[4] = {nullptr, nullptr, nullptr, nullptr};
  static Maps tm;
  if (key[0] != d_in[0] || key[1] != d_in[10] || key[2] != d_in[11] || key[3] != d_in[12]) {
    void* fn = nullptr; cudaDriverEntryPointQueryResult st;
    cudaGetDriverEntryPoint("cuTensorMapEncodeTiled", &fn, cudaEnableDefault, &st);
    EncFn f = (EncFn)fn;
    void *xt, *yt; cudaGetSymbolAddress(&xt, g_xt); cudaGetSymbolAddress(&yt, g_yt);
    const CUtensorMapSwizzle S128 = CU_TENSOR_MAP_SWIZZLE_128B;
    enc(f, &tm.xraw3, d_in[0], 3, 64, L_, 9, D_ * 2, 128, 64, 16, 9, S128);
    enc(f, &tm.x2, d_in[0], 2, D_, L_, 1, D_ * 2, 0, 64, 128, 1, S128);
    enc(f, &tm.xt64, xt, 3, 64, D_ / 4, 128, 128, 32 * D_, 64, 16, 8, S128);
    enc(f, &tm.xt8, xt, 3, 64, D_ / 4, 128, 128, 32 * D_, 64, 2, 8, S128);
    enc(f, &tm.xt, xt, 2, 16 * D_, 128, 1, 32 * D_, 0, 64, 128, 1, S128);
    enc(f, &tm.yt, yt, 2, L_, D_, 1, L_ * 2, 0, 64, 64, 1, S128);
    enc(f, &tm.w1, d_in[10], 2, F_, D_, 1, F_ * 2, 0, 64, 96, 1, S128);
    enc(f, &tm.w3, d_in[11], 2, F_, D_, 1, F_ * 2, 0, 64, 96, 1, S128);
    enc(f, &tm.w2, d_in[12], 2, D_, F_, 1, D_ * 2, 0, 64, 96, 1, S128);
    enc(f, &tm.x8, d_in[0], 2, D_, L_, 1, D_ * 2, 0, 8, 128, 1, CU_TENSOR_MAP_SWIZZLE_NONE);
    enc(f, &tm.yt8, yt, 2, L_, D_, 1, L_ * 2, 0, 64, 8, 1, S128);
    cudaFuncSetAttribute(k_main, cudaFuncAttributeMaxDynamicSharedMemorySize, SMEM_BYTES);
    key[0] = d_in[0]; key[1] = d_in[10]; key[2] = d_in[11]; key[3] = d_in[12];
  }
  SsmParams sp{(const __nv_bfloat16*)d_in[1], (const __nv_bfloat16*)d_in[2], (const __nv_bfloat16*)d_in[3], (const __nv_bfloat16*)d_in[4],
               (const __nv_bfloat16*)d_in[5], (const __nv_bfloat16*)d_in[6], (const __nv_bfloat16*)d_in[7]};
  k_main<<<NCTA, NTHR, SMEM_BYTES>>>(tm, sp, (const __nv_bfloat16*)d_in[8], (__nv_bfloat16*)d_out);
}
```
